```python
import torch

def _softmax(x, axis=-1):
    return torch.softmax(x, dim=axis)
def _gelu(x):
    return torch.nn.functional.gelu(x, approximate="tanh")
def _silu(x):
    return torch.nn.functional.silu(x)
def _sigmoid(x):
    return torch.sigmoid(x)
def _layernorm(x, axis=-1, eps=1e-5):
    m = x.mean(dim=axis, keepdim=True)
    v = x.var(dim=axis, keepdim=True, unbiased=False)
    return (x - m) / torch.sqrt(v + eps)
def _scatter_add(tgt, idx, src, axis=0):
    return tgt.clone().index_add_(axis, idx, src)
def _segment_sum(src, seg, n):
    out = torch.zeros((n,) + src.shape[1:], dtype=src.dtype)
    return out.index_add_(0, seg, src)
def _pad(x, pw):
    flat = tuple(v for pair in reversed(pw) for v in pair)
    return torch.nn.functional.pad(x, flat)

kernel_name = 'gated_mix__mha_block__glu_gated_bilinear__prompt'

def setup_inputs():

    _w = (lambda a: (lambda t: t.to(torch.bfloat16) if t.is_floating_point() else t)(torch.as_tensor(a)))
    def _A_setup():
        B, S, D, H = 1, 2048, 512, 32
        return {
            "x": _w((lambda *s: torch.randn(*s, dtype=torch.bfloat16) * 0.05)(B, S, D)),
            "wqkv": _w((lambda *s: torch.randn(*s, dtype=torch.bfloat16) * 0.8)(D, 3 * D)),
            "wo": _w((lambda *s: torch.randn(*s, dtype=torch.bfloat16) * 0.05)(D, D)),
        }
    _A_in = _A_setup()

    def _B_setup():
        B, S, D, F = 1, 2048, 512, 1376
        return {
            "x": _w((lambda *s: torch.randn(*s, dtype=torch.bfloat16) * 0.05)(B, S, D)),
            "w_gate": _w((lambda *s: torch.randn(*s, dtype=torch.bfloat16) * 1.6)(D, F) * (D ** -0.5)),
            "w_up": _w((lambda *s: torch.randn(*s, dtype=torch.bfloat16) * 1.6)(D, F) * (D ** -0.5)),
            "w_down": _w((lambda *s: torch.randn(*s, dtype=torch.bfloat16) * 1.6)(F, D) * (F ** -0.5)),
        }
    _B_in = _B_setup()

    return {
        "A_x": _A_in["x"],
        "A_wqkv": _A_in["wqkv"],
        "A_wo": _A_in["wo"],
        "B_x": _B_in["x"],
        "B_w_gate": _B_in["w_gate"],
        "B_w_up": _B_in["w_up"],
        "B_w_down": _B_in["w_down"],
        "gate_w": _w((lambda *s: torch.randn(*s, dtype=torch.bfloat16) * 0.05)(512) * 16.0),
    }

def reference(A_x, A_wqkv, A_wo, B_x, B_w_gate, B_w_up, B_w_down, gate_w):
    def _A_ref(x, wqkv, wo):
        B, S, D = x.shape
        H = 32
        Dh = D // H
        qkv = (lambda x, *d: x.permute(*d))((x @ wqkv).reshape(B, S, 3, H, Dh), 2, 0, 3, 1, 4)
        q, k, v = qkv[0], qkv[1], qkv[2]
        scores = torch.einsum("bhqd,bhkd->bhqk", q, k) * (Dh ** -0.5)
        p = _softmax(scores, axis=-1)
        o = torch.einsum("bhqk,bhkd->bhqd", p, v)
        return (lambda x, *d: x.permute(*d))(o, 0, 2, 1, 3).reshape(B, S, D) @ wo

    def _B_ref(x, w_gate, w_up, w_down):
        g = torch.einsum("bsd,df->bsf", x, w_gate)
        u = torch.einsum("bsd,df->bsf", x, w_up)
        h = g * u
        return torch.einsum("bsf,fd->bsd", h, w_down)

    x = A_x
    g = _sigmoid((x * gate_w).sum(-1, keepdims=True))
    a = _A_ref(x, A_wqkv, A_wo)
    b = _B_ref(x, B_w_gate, B_w_up, B_w_down)
    return g * a + (1 - g) * b
```

```cpp
#include <cuda_runtime.h>
#include <cuda.h>
#include <cuda_bf16.h>
#include <stdint.h>

namespace {

constexpr int SEQ = 2048;
constexpr int NCTA = 128;
constexpr int NTHREADS = 512;

constexpr uint32_t SM_X = 0;
constexpr uint32_t SM_RA = 131072;
constexpr uint32_t SM_RB = 131072 + 49152;
constexpr uint32_t SM_DR = 131072;
constexpr uint32_t SM_BP = 131072;
constexpr uint32_t SM_WO = 131072 + 32768;
constexpr uint32_t SM_ONES = 229376;
constexpr uint32_t SM_G = SM_ONES + 512;
constexpr uint32_t SM_BAR = SM_G + 512;
constexpr uint32_t SM_TOTAL = SM_BAR + 512;
constexpr int NA = 4, NB = 6, ND = 4;
enum {
    B_XFULL = 0, B_AFULL = B_XFULL + 8, B_AEMPTY = B_AFULL + NA, B_BFULL = B_AEMPTY + NA, B_BEMPTY = B_BFULL + NB,
    B_XFREE = B_BEMPTY + NB, B_KVFULL = B_XFREE + 1, B_DFULL = B_KVFULL + 8, B_DEMPTY = B_DFULL + ND,
    B_WOFULL = B_DEMPTY + ND, B_BREADY = B_WOFULL + 1, B_KVFREE = B_BREADY + 1,
    B_OFULL = B_KVFREE + 1, B_COUNT = B_OFULL + 8
};
static_assert(B_COUNT * 8 + 16 <= 512, "barrier area");

constexpr int PIECE = 2;
constexpr int SPLIT0 = 16 - 3 * PIECE;

__device__ __align__(1024) uint8_t g_Q[32 * SEQ * 32];
__device__ __align__(1024) uint8_t g_KV[32 * 16 * 8192];
__device__ __align__(1024) uint8_t g_Vb[32 * SEQ * 32];
__device__ __align__(1024) uint8_t g_H[16 * 22 * 16384];
__device__ __align__(1024) uint8_t g_O[16 * 8 * 16384];
__device__ __align__(1024) float g_gate[SEQ];
__device__ __align__(1024) float g_part[NCTA * 3 * 10 * 128];
__device__ __align__(1024) unsigned g_cnt[64 * 32];
constexpr int C_QKV = 0, C_H = 8, C_O = 24, C_EPOCH = 40;

__device__ __forceinline__ void wg_n112_tb(float (&d)[56], uint64_t da, uint64_t db, int sd) {
    asm volatile("{.reg .pred p; setp.ne.b32 p, %58, 0;\n"
        "wgmma.mma_async.sync.aligned.m64n112k16.f32.bf16.bf16 {%0, %1, %2, %3, %4, %5, %6, %7, %8, %9, %10, %11, %12, %13, %14, %15, %16, %17, %18, %19, %20, %21, %22, %23, %24, %25, %26, %27, %28, %29, %30, %31, %32, %33, %34, %35, %36, %37, %38, %39, %40, %41, %42, %43, %44, %45, %46, %47, %48, %49, %50, %51, %52, %53, %54, %55}, %56, %57, p, 1, 1, 0, 1;}"
        : "+f"(d[0]), "+f"(d[1]), "+f"(d[2]), "+f"(d[3]), "+f"(d[4]), "+f"(d[5]), "+f"(d[6]), "+f"(d[7]), "+f"(d[8]), "+f"(d[9]), "+f"(d[10]), "+f"(d[11]), "+f"(d[12]), "+f"(d[13]), "+f"(d[14]), "+f"(d[15]), "+f"(d[16]), "+f"(d[17]), "+f"(d[18]), "+f"(d[19]), "+f"(d[20]), "+f"(d[21]), "+f"(d[22]), "+f"(d[23]), "+f"(d[24]), "+f"(d[25]), "+f"(d[26]), "+f"(d[27]), "+f"(d[28]), "+f"(d[29]), "+f"(d[30]), "+f"(d[31]), "+f"(d[32]), "+f"(d[33]), "+f"(d[34]), "+f"(d[35]), "+f"(d[36]), "+f"(d[37]), "+f"(d[38]), "+f"(d[39]), "+f"(d[40]), "+f"(d[41]), "+f"(d[42]), "+f"(d[43]), "+f"(d[44]), "+f"(d[45]), "+f"(d[46]), "+f"(d[47]), "+f"(d[48]), "+f"(d[49]), "+f"(d[50]), "+f"(d[51]), "+f"(d[52]), "+f"(d[53]), "+f"(d[54]), "+f"(d[55])
        : "l"(da), "l"(db), "r"(sd));
}
__device__ __forceinline__ void wg_n128_tb(float (&d)[64], uint64_t da, uint64_t db, int sd) {
    asm volatile("{.reg .pred p; setp.ne.b32 p, %66, 0;\n"
        "wgmma.mma_async.sync.aligned.m64n128k16.f32.bf16.bf16 {%0, %1, %2, %3, %4, %5, %6, %7, %8, %9, %10, %11, %12, %13, %14, %15, %16, %17, %18, %19, %20, %21, %22, %23, %24, %25, %26, %27, %28, %29, %30, %31, %32, %33, %34, %35, %36, %37, %38, %39, %40, %41, %42, %43, %44, %45, %46, %47, %48, %49, %50, %51, %52, %53, %54, %55, %56, %57, %58, %59, %60, %61, %62, %63}, %64, %65, p, 1, 1, 0, 1;}"
        : "+f"(d[0]), "+f"(d[1]), "+f"(d[2]), "+f"(d[3]), "+f"(d[4]), "+f"(d[5]), "+f"(d[6]), "+f"(d[7]), "+f"(d[8]), "+f"(d[9]), "+f"(d[10]), "+f"(d[11]), "+f"(d[12]), "+f"(d[13]), "+f"(d[14]), "+f"(d[15]), "+f"(d[16]), "+f"(d[17]), "+f"(d[18]), "+f"(d[19]), "+f"(d[20]), "+f"(d[21]), "+f"(d[22]), "+f"(d[23]), "+f"(d[24]), "+f"(d[25]), "+f"(d[26]), "+f"(d[27]), "+f"(d[28]), "+f"(d[29]), "+f"(d[30]), "+f"(d[31]), "+f"(d[32]), "+f"(d[33]), "+f"(d[34]), "+f"(d[35]), "+f"(d[36]), "+f"(d[37]), "+f"(d[38]), "+f"(d[39]), "+f"(d[40]), "+f"(d[41]), "+f"(d[42]), "+f"(d[43]), "+f"(d[44]), "+f"(d[45]), "+f"(d[46]), "+f"(d[47]), "+f"(d[48]), "+f"(d[49]), "+f"(d[50]), "+f"(d[51]), "+f"(d[52]), "+f"(d[53]), "+f"(d[54]), "+f"(d[55]), "+f"(d[56]), "+f"(d[57]), "+f"(d[58]), "+f"(d[59]), "+f"(d[60]), "+f"(d[61]), "+f"(d[62]), "+f"(d[63])
        : "l"(da), "l"(db), "r"(sd));
}
__device__ __forceinline__ void wg_n48_tb(float (&d)[24], uint64_t da, uint64_t db, int sd) {
    asm volatile("{.reg .pred p; setp.ne.b32 p, %26, 0;\n"
        "wgmma.mma_async.sync.aligned.m64n48k16.f32.bf16.bf16 {%0, %1, %2, %3, %4, %5, %6, %7, %8, %9, %10, %11, %12, %13, %14, %15, %16, %17, %18, %19, %20, %21, %22, %23}, %24, %25, p, 1, 1, 0, 1;}"
        : "+f"(d[0]), "+f"(d[1]), "+f"(d[2]), "+f"(d[3]), "+f"(d[4]), "+f"(d[5]), "+f"(d[6]), "+f"(d[7]), "+f"(d[8]), "+f"(d[9]), "+f"(d[10]), "+f"(d[11]), "+f"(d[12]), "+f"(d[13]), "+f"(d[14]), "+f"(d[15]), "+f"(d[16]), "+f"(d[17]), "+f"(d[18]), "+f"(d[19]), "+f"(d[20]), "+f"(d[21]), "+f"(d[22]), "+f"(d[23])
        : "l"(da), "l"(db), "r"(sd));
}
__device__ __forceinline__ void wg_n128_ta(float (&d)[64], uint64_t da, uint64_t db, int sd) {
    asm volatile("{.reg .pred p; setp.ne.b32 p, %66, 0;\n"
        "wgmma.mma_async.sync.aligned.m64n128k16.f32.bf16.bf16 {%0, %1, %2, %3, %4, %5, %6, %7, %8, %9, %10, %11, %12, %13, %14, %15, %16, %17, %18, %19, %20, %21, %22, %23, %24, %25, %26, %27, %28, %29, %30, %31, %32, %33, %34, %35, %36, %37, %38, %39, %40, %41, %42, %43, %44, %45, %46, %47, %48, %49, %50, %51, %52, %53, %54, %55, %56, %57, %58, %59, %60, %61, %62, %63}, %64, %65, p, 1, 1, 1, 0;}"
        : "+f"(d[0]), "+f"(d[1]), "+f"(d[2]), "+f"(d[3]), "+f"(d[4]), "+f"(d[5]), "+f"(d[6]), "+f"(d[7]), "+f"(d[8]), "+f"(d[9]), "+f"(d[10]), "+f"(d[11]), "+f"(d[12]), "+f"(d[13]), "+f"(d[14]), "+f"(d[15]), "+f"(d[16]), "+f"(d[17]), "+f"(d[18]), "+f"(d[19]), "+f"(d[20]), "+f"(d[21]), "+f"(d[22]), "+f"(d[23]), "+f"(d[24]), "+f"(d[25]), "+f"(d[26]), "+f"(d[27]), "+f"(d[28]), "+f"(d[29]), "+f"(d[30]), "+f"(d[31]), "+f"(d[32]), "+f"(d[33]), "+f"(d[34]), "+f"(d[35]), "+f"(d[36]), "+f"(d[37]), "+f"(d[38]), "+f"(d[39]), "+f"(d[40]), "+f"(d[41]), "+f"(d[42]), "+f"(d[43]), "+f"(d[44]), "+f"(d[45]), "+f"(d[46]), "+f"(d[47]), "+f"(d[48]), "+f"(d[49]), "+f"(d[50]), "+f"(d[51]), "+f"(d[52]), "+f"(d[53]), "+f"(d[54]), "+f"(d[55]), "+f"(d[56]), "+f"(d[57]), "+f"(d[58]), "+f"(d[59]), "+f"(d[60]), "+f"(d[61]), "+f"(d[62]), "+f"(d[63])
        : "l"(da), "l"(db), "r"(sd));
}
__device__ __forceinline__ void wg_n64_ta(float (&d)[32], uint64_t da, uint64_t db, int sd) {
    asm volatile("{.reg .pred p; setp.ne.b32 p, %34, 0;\n"
        "wgmma.mma_async.sync.aligned.m64n64k16.f32.bf16.bf16 {%0, %1, %2, %3, %4, %5, %6, %7, %8, %9, %10, %11, %12, %13, %14, %15, %16, %17, %18, %19, %20, %21, %22, %23, %24, %25, %26, %27, %28, %29, %30, %31}, %32, %33, p, 1, 1, 1, 0;}"
        : "+f"(d[0]), "+f"(d[1]), "+f"(d[2]), "+f"(d[3]), "+f"(d[4]), "+f"(d[5]), "+f"(d[6]), "+f"(d[7]), "+f"(d[8]), "+f"(d[9]), "+f"(d[10]), "+f"(d[11]), "+f"(d[12]), "+f"(d[13]), "+f"(d[14]), "+f"(d[15]), "+f"(d[16]), "+f"(d[17]), "+f"(d[18]), "+f"(d[19]), "+f"(d[20]), "+f"(d[21]), "+f"(d[22]), "+f"(d[23]), "+f"(d[24]), "+f"(d[25]), "+f"(d[26]), "+f"(d[27]), "+f"(d[28]), "+f"(d[29]), "+f"(d[30]), "+f"(d[31])
        : "l"(da), "l"(db), "r"(sd));
}
__device__ __forceinline__ void wg_qk_n64(float (&d)[32], const uint32_t (&a)[4], uint64_t db) {
    asm volatile("wgmma.mma_async.sync.aligned.m64n64k16.f32.bf16.bf16 {%0, %1, %2, %3, %4, %5, %6, %7, %8, %9, %10, %11, %12, %13, %14, %15, %16, %17, %18, %19, %20, %21, %22, %23, %24, %25, %26, %27, %28, %29, %30, %31}, {%32,%33,%34,%35}, %36, 0, 1, 1, 0;"
        : "=f"(d[0]), "=f"(d[1]), "=f"(d[2]), "=f"(d[3]), "=f"(d[4]), "=f"(d[5]), "=f"(d[6]), "=f"(d[7]), "=f"(d[8]), "=f"(d[9]), "=f"(d[10]), "=f"(d[11]), "=f"(d[12]), "=f"(d[13]), "=f"(d[14]), "=f"(d[15]), "=f"(d[16]), "=f"(d[17]), "=f"(d[18]), "=f"(d[19]), "=f"(d[20]), "=f"(d[21]), "=f"(d[22]), "=f"(d[23]), "=f"(d[24]), "=f"(d[25]), "=f"(d[26]), "=f"(d[27]), "=f"(d[28]), "=f"(d[29]), "=f"(d[30]), "=f"(d[31])
        : "r"(a[0]), "r"(a[1]), "r"(a[2]), "r"(a[3]), "l"(db));
}
__device__ __forceinline__ void wg_pv_n24(float (&d)[12], uint32_t a0, uint32_t a1, uint32_t a2, uint32_t a3, uint64_t db) {
    asm volatile("wgmma.mma_async.sync.aligned.m64n24k16.f32.f16.f16 {%0, %1, %2, %3, %4, %5, %6, %7, %8, %9, %10, %11}, {%12,%13,%14,%15}, %16, 1, 1, 1, 1;"
        : "+f"(d[0]), "+f"(d[1]), "+f"(d[2]), "+f"(d[3]), "+f"(d[4]), "+f"(d[5]), "+f"(d[6]), "+f"(d[7]), "+f"(d[8]), "+f"(d[9]), "+f"(d[10]), "+f"(d[11])
        : "r"(a0), "r"(a1), "r"(a2), "r"(a3), "l"(db));
}

__device__ __forceinline__ void wg_fence() { asm volatile("wgmma.fence.sync.aligned;" ::: "memory"); }
__device__ __forceinline__ void wg_commit() { asm volatile("wgmma.commit_group.sync.aligned;" ::: "memory"); }
template <int N> __device__ __forceinline__ void wg_wait() { asm volatile("wgmma.wait_group.sync.aligned %0;" ::"n"(N) : "memory"); }
template <int N> __device__ __forceinline__ void fence_regs(float (&d)[N]) {
#pragma unroll
    for (int i = 0; i < N; i++) asm volatile("" : "+f"(d[i])::"memory");
}
__device__ __forceinline__ uint64_t mkdesc(uint32_t addr, uint32_t lbo, uint32_t sbo, uint32_t sw) {
    return (uint64_t)((addr & 0x3FFFF) >> 4) | ((uint64_t)((lbo & 0x3FFFF) >> 4) << 16) | ((uint64_t)(sbo >> 4) << 32) | ((uint64_t)sw << 62);
}
__device__ __forceinline__ void mbar_init(uint32_t a, uint32_t c) { asm volatile("mbarrier.init.shared::cta.b64 [%0], %1;" ::"r"(a), "r"(c) : "memory"); }
__device__ __forceinline__ void mbar_expect(uint32_t a, uint32_t b) { asm volatile("mbarrier.arrive.expect_tx.shared::cta.b64 _, [%0], %1;" ::"r"(a), "r"(b) : "memory"); }
__device__ __forceinline__ void mbar_arrive(uint32_t a) { asm volatile("mbarrier.arrive.shared::cta.b64 _, [%0];" ::"r"(a) : "memory"); }
__device__ __forceinline__ void mbar_wait(uint32_t a, uint32_t ph) {
    asm volatile("{.reg .pred p; .reg .u32 t0, t1;\n"
                 "mbarrier.try_wait.parity.shared::cta.b64 p, [%0], %1;\n"
                 "@p bra.uni WD%=;\n"
                 "mov.u32 t0, %%clock;\n"
                 "WL%=:\n"
                 "mbarrier.try_wait.parity.shared::cta.b64 p, [%0], %1;\n"
                 "@p bra.uni WD%=;\n"
                 "mov.u32 t1, %%clock;\n"
                 "sub.u32 t1, t1, t0;\n"
                 "setp.lt.u32 p, t1, 0x10000000;\n"
                 "@p bra.uni WL%=;\n"
                 "WD%=:}" ::"r"(a), "r"(ph) : "memory");
}
__device__ __forceinline__ void tma2d(uint32_t dst, const CUtensorMap* tm, uint32_t bar, int x, int y) {
    asm volatile("cp.async.bulk.tensor.2d.shared::cluster.global.mbarrier::complete_tx::bytes [%0], [%1, {%3, %4}], [%2];"
                 ::"r"(dst), "l"(tm), "r"(bar), "r"(x), "r"(y) : "memory");
}
__device__ __forceinline__ void bulk_load(uint32_t dst, const void* src, uint32_t bytes, uint32_t bar) {
    asm volatile("cp.async.bulk.shared::cluster.global.mbarrier::complete_tx::bytes [%0], [%1], %2, [%3];"
                 ::"r"(dst), "l"(src), "r"(bytes), "r"(bar) : "memory");
}
__device__ __forceinline__ void proxy_fence() { asm volatile("fence.proxy.async;" ::: "memory"); }
__device__ __forceinline__ void wg_bar(int wg) { asm volatile("bar.sync %0, 128;" ::"r"(wg + 1) : "memory"); }
__device__ __forceinline__ bool wg_any(int wg, bool v) {
    uint32_t r;
    asm volatile("{.reg .pred p, q; setp.ne.u32 p, %2, 0; bar.red.or.pred q, %1, 128, p; selp.u32 %0, 1, 0, q;}" : "=r"(r) : "r"(wg + 1), "r"((uint32_t)v) : "memory");
    return r;
}
__device__ __forceinline__ void cnt_signal(int idx) {
    asm volatile("red.release.gpu.global.add.u32 [%0], 1;" ::"l"(&g_cnt[idx * 32]) : "memory");
}
__device__ __forceinline__ void cnt_wait(int idx, unsigned target) {
    for (uint32_t n = 0; n < (1u << 20); n++) {
        unsigned v;
        asm volatile("ld.acquire.gpu.global.u32 %0, [%1];" : "=r"(v) : "l"(&g_cnt[idx * 32]) : "memory");
        if ((int)(v - target) >= 0) break;
        __nanosleep(20);
    }
    proxy_fence();
}
__device__ __forceinline__ void wg_publish(int wg, int idx, bool leader) {
    proxy_fence();
    wg_bar(wg);
    if (leader) cnt_signal(idx);
}
__device__ __forceinline__ float ex2(float x) { float y; asm("ex2.approx.ftz.f32 %0, %1;" : "=f"(y) : "f"(x)); return y; }
__device__ __forceinline__ uint32_t pack_bf16(float lo, float hi) { uint32_t y; asm("cvt.rn.bf16x2.f32 %0, %1, %2;" : "=r"(y) : "f"(hi), "f"(lo)); return y; }
__device__ __forceinline__ uint32_t pack_f16(float lo, float hi) { uint32_t y; asm("cvt.rn.f16x2.f32 %0, %1, %2;" : "=r"(y) : "f"(hi), "f"(lo)); return y; }
__device__ __forceinline__ uint32_t hfma2(uint32_t a, uint32_t b, uint32_t c) { uint32_t y; asm("fma.rn.f16x2 %0, %1, %2, %3;" : "=r"(y) : "r"(a), "r"(b), "r"(c)); return y; }
__device__ __forceinline__ float bf_lo(uint32_t v) { return __uint_as_float(v << 16); }
__device__ __forceinline__ float bf_hi(uint32_t v) { return __uint_as_float(v & 0xFFFF0000u); }
__device__ __forceinline__ float bf_round(float v) { return bf_lo(pack_bf16(v, 0.f)); }
__device__ __forceinline__ void st8(void* p, uint32_t a, uint32_t b) { asm volatile("st.global.v2.u32 [%0], {%1, %2};" ::"l"(p), "r"(a), "r"(b) : "memory"); }
__device__ __forceinline__ void st4(void* p, uint32_t a) { asm volatile("st.global.u32 [%0], %1;" ::"l"(p), "r"(a) : "memory"); }
__device__ __forceinline__ uint32_t ld4(const void* p) { uint32_t v; asm volatile("ld.global.cg.u32 %0, [%1];" : "=r"(v) : "l"(p) : "memory"); return v; }

__device__ __forceinline__ uint32_t exp2_pair_fma(float x0, float x1, uint32_t one2) {
    float t0, t1;
    asm("fma.rn.f32 %0, %1, 0f00000400, 0f00003C00;" : "=f"(t0) : "f"(x0));
    asm("fma.rn.f32 %0, %1, 0f00000400, 0f00003C00;" : "=f"(t1) : "f"(x1));
    uint32_t u, g;
    asm("cvt.pack.sat.s16.s32 %0, %1, %2;" : "=r"(u) : "r"(__float_as_int(t1)), "r"(__float_as_int(t0)));
    asm("lop3.b32 %0, %1, 0x03FF03FF, %2, 0xEA;" : "=r"(g) : "r"(u), "r"(one2));
    uint32_t p = hfma2(0x2d012d01u, g, 0xa082a082u);
    p = hfma2(p, g, 0x37ab37abu);
    p = hfma2(p, g, 0x37383738u);
    return p + u - g;
}
constexpr uint32_t POLY_MASK = 0x5755;
__device__ __forceinline__ void softmax_tile(const float (&s)[32], uint32_t (&p)[16], uint32_t one2) {
#pragma unroll
    for (int i = 0; i < 16; i++) {
        if ((POLY_MASK >> i) & 1) p[i] = exp2_pair_fma(s[2 * i], s[2 * i + 1], one2);
        else p[i] = pack_f16(ex2(s[2 * i]), ex2(s[2 * i + 1]));
    }
}
constexpr uint64_t VSTEP16 = 32ull - (32ull << 16);
__device__ __forceinline__ void pv_tile(float (&o)[12], const uint32_t (&p)[16], uint64_t v) {
#pragma unroll
    for (int kk = 0; kk < 4; kk++) wg_pv_n24(o, p[4 * kk], p[4 * kk + 1], p[4 * kk + 2], p[4 * kk + 3], v + kk * VSTEP16);
}

__device__ __forceinline__ void attn_fast(float (&o)[12], const uint32_t (&qa)[4], uint32_t sb, int c0, int c1, uint32_t one2) {
    constexpr uint64_t KT = 128;
    constexpr uint64_t KU = 512;
    constexpr uint64_t VT = 4 * VSTEP16;
    constexpr uint64_t VU = 512ull - (512ull << 16);
    uint32_t ka = sb + SM_X + c0 * 8192, va = ka + 4096;
    uint64_t k = mkdesc(ka, 16, 256, 3);
    uint64_t v = mkdesc(va, sb + SM_ONES - va, 256, 3);
    float s[32];
    uint32_t p0[16], p1[16];
    fence_regs(o);
    wg_fence();
    wg_qk_n64(s, qa, k);
    wg_commit();
    wg_wait<0>();
    softmax_tile(s, p0, one2);
#pragma unroll 1
    for (int c = c0; c < c1 - 1; c++) {
        wg_fence();
        wg_qk_n64(s, qa, k + KT);
        wg_commit();
        pv_tile(o, p0, v);
        wg_commit();
        wg_wait<1>();
        softmax_tile(s, p1, one2);
        wg_wait<0>();
        wg_fence();
        wg_qk_n64(s, qa, k + KU);
        wg_commit();
        pv_tile(o, p1, v + VT);
        wg_commit();
        wg_wait<1>();
        softmax_tile(s, p0, one2);
        wg_wait<0>();
        k += KU; v += VU;
    }
    wg_fence();
    wg_qk_n64(s, qa, k + KT);
    wg_commit();
    pv_tile(o, p0, v);
    wg_commit();
    wg_wait<1>();
    softmax_tile(s, p1, one2);
    wg_fence();
    pv_tile(o, p1, v + VT);
    wg_commit();
    wg_wait<0>();
    fence_regs(o);
}

__device__ __forceinline__ void mma_bf16(float (&d)[4], const uint32_t (&a)[4], uint32_t b0, uint32_t b1) {
    asm volatile("mma.sync.aligned.m16n8k16.row.col.f32.bf16.bf16.f32 {%0,%1,%2,%3}, {%4,%5,%6,%7}, {%8,%9}, {%0,%1,%2,%3};"
                 : "+f"(d[0]), "+f"(d[1]), "+f"(d[2]), "+f"(d[3]) : "r"(a[0]), "r"(a[1]), "r"(a[2]), "r"(a[3]), "r"(b0), "r"(b1));
}
__device__ __forceinline__ uint32_t movm(uint32_t a) { uint32_t d; asm volatile("movmatrix.sync.aligned.m8n8.trans.b16 %0, %1;" : "=r"(d) : "r"(a)); return d; }

__device__ __noinline__ void attn_generic(float* o_out, uint32_t q0, uint32_t q1, uint32_t q2, uint32_t q3, uint32_t sb, int head) {
    const int lane = threadIdx.x & 31, g = lane >> 2, t = lane & 3;
    const uint32_t qa[4] = {q0, q1, q2, q3};
    float oa[4] = {0, 0, 0, 0}, ob[4] = {0, 0, 0, 0};
    float m0 = -INFINITY, m1 = -INFINITY, l0 = 0.f, l1 = 0.f;
    const uint8_t* vb = g_Vb + (size_t)head * SEQ * 32;
#pragma unroll 1
    for (int kb = 0; kb < SEQ / 16; kb++) {
        float sa[4] = {0, 0, 0, 0}, sc[4] = {0, 0, 0, 0};
#pragma unroll
        for (int h = 0; h < 2; h++) {
            int key = kb * 16 + h * 8 + g, kl = key & 127, sw = (kl >> 2) & 1;
            uint32_t ra = sb + SM_X + (key >> 7) * 8192 + kl * 32 + t * 4, b0, b1;
            asm volatile("ld.shared.u32 %0, [%1];" : "=r"(b0) : "r"(ra + sw * 16));
            asm volatile("ld.shared.u32 %0, [%1];" : "=r"(b1) : "r"(ra + (sw ^ 1) * 16));
            if (h == 0) mma_bf16(sa, qa, b0, b1); else mma_bf16(sc, qa, b0, b1);
        }
        float x0 = fmaxf(fmaxf(sa[0], sa[1]), fmaxf(sc[0], sc[1])), x1 = fmaxf(fmaxf(sa[2], sa[3]), fmaxf(sc[2], sc[3]));
        x0 = fmaxf(x0, __shfl_xor_sync(~0u, x0, 1)); x0 = fmaxf(x0, __shfl_xor_sync(~0u, x0, 2));
        x1 = fmaxf(x1, __shfl_xor_sync(~0u, x1, 1)); x1 = fmaxf(x1, __shfl_xor_sync(~0u, x1, 2));
        float n0 = fmaxf(m0, x0), n1 = fmaxf(m1, x1);
        float a0 = ex2(m0 - n0), a1 = ex2(m1 - n1);
        m0 = n0; m1 = n1;
        float e0 = ex2(sa[0] - n0), e1 = ex2(sa[1] - n0), e2 = ex2(sa[2] - n1), e3 = ex2(sa[3] - n1);
        float f0 = ex2(sc[0] - n0), f1 = ex2(sc[1] - n0), f2 = ex2(sc[2] - n1), f3 = ex2(sc[3] - n1);
        l0 = l0 * a0 + (e0 + e1) + (f0 + f1);
        l1 = l1 * a1 + (e2 + e3) + (f2 + f3);
        oa[0] *= a0; oa[1] *= a0; oa[2] *= a1; oa[3] *= a1;
        ob[0] *= a0; ob[1] *= a0; ob[2] *= a1; ob[3] *= a1;
        const uint32_t pa[4] = {pack_bf16(e0, e1), pack_bf16(e2, e3), pack_bf16(f0, f1), pack_bf16(f2, f3)};
        const uint8_t* vr = vb + (size_t)(kb * 16 + g) * 32 + t * 4;
        uint32_t v00 = movm(ld4(vr)), v01 = movm(ld4(vr + 256)), v10 = movm(ld4(vr + 16)), v11 = movm(ld4(vr + 256 + 16));
        mma_bf16(oa, pa, v00, v01);
        mma_bf16(ob, pa, v10, v11);
    }
    l0 += __shfl_xor_sync(~0u, l0, 1); l0 += __shfl_xor_sync(~0u, l0, 2);
    l1 += __shfl_xor_sync(~0u, l1, 1); l1 += __shfl_xor_sync(~0u, l1, 2);
    o_out[0] = oa[0]; o_out[1] = oa[1]; o_out[2] = oa[2]; o_out[3] = oa[3];
    o_out[4] = ob[0]; o_out[5] = ob[1]; o_out[6] = ob[2]; o_out[7] = ob[3];
    o_out[8] = l0; o_out[9] = l1;
}

__device__ __forceinline__ void store_h(uint8_t* hrow, int col, int g, float a0, float a1, float b0, float b1) {
    uint8_t* p = hrow + (col >> 6) * 16384 + ((((col >> 3) & 7) ^ g) << 4);
    st4(p, pack_bf16(a0, a1));
    st4(p + 1024, pack_bf16(b0, b1));
}

struct Params {
    const uint4* x;
    const uint4* gate_w;
};

__global__ void __launch_bounds__(NTHREADS, 1)
fused_kernel(const __grid_constant__ CUtensorMap tmX, const __grid_constant__ CUtensorMap tmQKV,
             const __grid_constant__ CUtensorMap tmG, const __grid_constant__ CUtensorMap tmU,
             const __grid_constant__ CUtensorMap tmD, const __grid_constant__ CUtensorMap tmWO,
             const __grid_constant__ CUtensorMap tmOut, const uint4* __restrict__ xg, const uint4* __restrict__ gw) {
    extern __shared__ __align__(1024) uint8_t smem[];
    const uint32_t sb = (uint32_t)__cvta_generic_to_shared(smem);
    const uint32_t bar = sb + SM_BAR;
    const int tid = threadIdx.x, lane = tid & 31;
    const int wg = __shfl_sync(~0u, tid >> 7, 0), w = __shfl_sync(~0u, (tid >> 5) & 3, 0);
    const int rb = blockIdx.x >> 3, cg = blockIdx.x & 7;
    const int head = blockIdx.x >> 2, qq = blockIdx.x & 3;

    if (tid == 0) {
        for (int i = 0; i < B_COUNT; i++) {
            uint32_t c = 1;
            if ((i >= B_AEMPTY && i < B_AEMPTY + NA) || (i >= B_BEMPTY && i < B_BEMPTY + NB)) c = 8;
            if (i == B_XFREE || i == B_KVFREE) c = 16;
            if ((i >= B_DEMPTY && i < B_DEMPTY + ND) || i == B_WOFULL || i == B_BREADY) c = 4;
            mbar_init(bar + 8 * i, c);
        }
        asm volatile("fence.mbarrier_init.release.cluster;" ::: "memory");
    }
    if (tid >= 128 && tid < 256) *(uint32_t*)(smem + SM_ONES + (tid - 128) * 4) = 0x3C003C00u;
    asm volatile("fence.proxy.async.shared::cta;" ::: "memory");
    unsigned epoch;
    asm volatile("ld.relaxed.gpu.global.u32 %0, [%1];" : "=r"(epoch) : "l"(&g_cnt[C_EPOCH * 32]) : "memory");
    __syncthreads();

    {
        const int g = lane >> 2, t = lane & 3;
        const int mi = wg & 1;
        const int nsl = wg < 2 ? NA : NB;
        const uint32_t fullb = bar + 8 * (wg < 2 ? B_AFULL : B_BFULL), emptyb = bar + 8 * (wg < 2 ? B_AEMPTY : B_BEMPTY);
        const int pw = mi * 4 + w;
        auto ring_issue = [&](int st, int sl) {
            const uint32_t fb = fullb + 8 * sl;
            const int k0 = (st & 15) * 32;
            if (wg < 2) {
                const uint32_t dst = sb + SM_RA + sl * 12288;
                if (st < 16) {
                    mbar_expect(fb, 12288);
                    tma2d(dst, &tmQKV, fb, 1024 + cg * 64, k0);
                    tma2d(dst + 4096, &tmG, fb, cg * 176 + 128, k0);
                    tma2d(dst + 8192, &tmU, fb, cg * 176 + 128, k0);
                } else {
                    mbar_expect(fb, 8192);
                    tma2d(dst, &tmG, fb, cg * 176 + 64, k0);
                    tma2d(dst + 4096, &tmU, fb, cg * 176 + 64, k0);
                }
            } else {
                const uint32_t dst = sb + SM_RB + sl * 8192;
                mbar_expect(fb, 8192);
                tma2d(dst, st < 16 ? &tmQKV : &tmG, fb, st < 16 ? cg * 64 : cg * 176, k0);
                tma2d(dst + 4096, st < 16 ? &tmQKV : &tmU, fb, st < 16 ? 512 + cg * 64 : cg * 176, k0);
            }
        };
        auto ring_release = [&](int st, int sl, int ph) {
            if (lane == 0) {
                mbar_arrive(emptyb + 8 * sl);
                if (st + nsl < 32 && ((st + nsl) & 7) == pw) {
                    mbar_wait(emptyb + 8 * sl, ph);
                    ring_issue(st + nsl, sl);
                }
            }
            __syncwarp();
        };
        if (lane == 0) {
            if (!(w & 1)) {
                const int xb = (w >> 1) * 4 + wg;
                mbar_expect(bar + 8 * (B_XFULL + xb), 16384);
                tma2d(sb + SM_X + xb * 16384, &tmX, bar + 8 * (B_XFULL + xb), xb * 64, rb * 128);
            }
            if (pw < nsl) ring_issue(pw, pw);
        }
        __syncwarp();
        {
            const int row = rb * 128 + cg * 16 + wg * 4 + w;
            const uint4 xa = __ldg(xg + row * 64 + lane), xb = __ldg(xg + row * 64 + 32 + lane);
            const uint4 ga = __ldg(gw + lane), gb = __ldg(gw + 32 + lane);
            const uint32_t xs[8] = {xa.x, xa.y, xa.z, xa.w, xb.x, xb.y, xb.z, xb.w};
            const uint32_t gs[8] = {ga.x, ga.y, ga.z, ga.w, gb.x, gb.y, gb.z, gb.w};
            float z = 0.f;
#pragma unroll
            for (int i = 0; i < 8; i++) {
                uint32_t pr = pack_bf16(bf_lo(xs[i]) * bf_lo(gs[i]), bf_hi(xs[i]) * bf_hi(gs[i]));
                z += bf_lo(pr) + bf_hi(pr);
            }
#pragma unroll
            for (int o = 16; o; o >>= 1) z += __shfl_xor_sync(~0u, z, o);
            z = bf_round(z);
            if (lane == 0) g_gate[row] = bf_round(1.f / (1.f + __expf(-z)));
        }
        const uint64_t dX = mkdesc(sb + SM_X + mi * 8192, 16, 1024, 1);
        const int lrow = mi * 64 + w * 16 + g;
        uint8_t* const hrow = g_H + (size_t)rb * 22 * 16384 + lrow * 128 + t * 4;
        const size_t r0 = (size_t)(cg * 4) * SEQ + rb * 128 + lrow;
        uint8_t* const kp = g_KV + ((size_t)(cg * 4) * 16 + rb) * 8192 + lrow * 32 + (((t >> 1) ^ ((g >> 2) & 1)) << 4) + (t & 1) * 8;
        const uint64_t dR = mkdesc(sb + (wg < 2 ? SM_RA : SM_RB), 4096, 1024, 1);
        const int slstep = wg < 2 ? 768 : 512;
        int sl = 0, ph = 0, prev = 0, pph = 0;
        if (wg < 2) {
            float av[56], au[24];
#pragma unroll 1
            for (int s = 0; s < 16; s++) {
                if (!(s & 1)) mbar_wait(bar + 8 * (B_XFULL + (s >> 1)), 0);
                mbar_wait(fullb + 8 * sl, ph);
                const uint64_t a = dX + (s >> 1) * 1024 + (s & 1) * 4, b = dR + sl * 768;
                wg_fence();
                wg_n112_tb(av, a, b, s);
                wg_n48_tb(au, a, b + 512, s);
                wg_n112_tb(av, a + 2, b + 128, 1);
                wg_n48_tb(au, a + 2, b + 512 + 128, 1);
                wg_commit();
                wg_wait<1>();
                if (s) ring_release(s - 1, prev, pph);
                prev = sl; pph = ph;
                if (++sl == NA) { sl = 0; ph ^= 1; }
            }
            wg_wait<0>();
            fence_regs(av); fence_regs(au);
            ring_release(15, prev, pph);
            uint8_t* vp = g_Vb + r0 * 32 + t * 8;
#pragma unroll
            for (int h = 0; h < 4; h++) {
                const float* v = av + h * 8;
                st8(kp + h * 131072 + 4096, pack_f16(v[0], v[1]), pack_f16(v[4], v[5]));
                st8(kp + h * 131072 + 4096 + 256, pack_f16(v[2], v[3]), pack_f16(v[6], v[7]));
                st8(vp + h * (SEQ * 32), pack_bf16(v[0], v[1]), pack_bf16(v[4], v[5]));
                st8(vp + h * (SEQ * 32) + 256, pack_bf16(v[2], v[3]), pack_bf16(v[6], v[7]));
            }
#pragma unroll
            for (int j = 0; j < 6; j++)
                store_h(hrow, cg * 176 + 128 + j * 8, g, av[32 + 4 * j] * au[4 * j], av[33 + 4 * j] * au[4 * j + 1],
                        av[34 + 4 * j] * au[4 * j + 2], av[35 + 4 * j] * au[4 * j + 3]);
            wg_publish(wg, C_QKV + cg, (tid & 127) == 0);
        }
#pragma unroll 1
        for (int tile = (wg < 2); tile < 2; tile++) {
            float acc[64];
#pragma unroll 1
            for (int s = 0; s < 16; s++) {
                if (!(s & 1)) mbar_wait(bar + 8 * (B_XFULL + (s >> 1)), 0);
                mbar_wait(fullb + 8 * sl, ph);
                const uint64_t a = dX + (s >> 1) * 1024 + (s & 1) * 4, b = dR + sl * slstep;
                wg_fence();
                wg_n128_tb(acc, a, b, s);
                wg_n128_tb(acc, a + 2, b + 128, 1);
                wg_commit();
                wg_wait<1>();
                if (s) ring_release(tile * 16 + s - 1, prev, pph);
                prev = sl; pph = ph;
                if (++sl == nsl) { sl = 0; ph ^= 1; }
            }
            wg_wait<0>();
            fence_regs(acc);
            if (tile == 0) {
                ring_release(15, prev, pph);
                const float qs = 0.25f * 1.4426950408889634f;
                uint8_t* qp = g_Q + r0 * 32 + t * 8;
#pragma unroll
                for (int h = 0; h < 4; h++) {
                    const float* q = acc + h * 8; const float* k = acc + 32 + h * 8;
                    st8(qp + h * (SEQ * 32), pack_bf16(q[0] * qs, q[1] * qs), pack_bf16(q[4] * qs, q[5] * qs));
                    st8(qp + h * (SEQ * 32) + 256, pack_bf16(q[2] * qs, q[3] * qs), pack_bf16(q[6] * qs, q[7] * qs));
                    st8(kp + h * 131072, pack_bf16(k[0], k[1]), pack_bf16(k[4], k[5]));
                    st8(kp + h * 131072 + 256, pack_bf16(k[2], k[3]), pack_bf16(k[6], k[7]));
                }
                wg_publish(wg, C_QKV + cg, (tid & 127) == 0);
            } else {
                if (lane == 0) {
                    mbar_arrive(bar + 8 * B_XFREE);
                    if (wg < 2) {
                        const int j = (pw + (SPLIT0 >> 1)) & 7;
                        cnt_wait(C_QKV + (head >> 2), (epoch + 1) * 64);
                        mbar_wait(bar + 8 * B_XFREE, 0);
                        mbar_expect(bar + 8 * (B_KVFULL + j), 16384);
                        bulk_load(sb + SM_X + j * 16384, g_KV + (size_t)head * 131072 + j * 16384, 16384, bar + 8 * (B_KVFULL + j));
                    }
                }
                __syncwarp();
                const int col0 = cg * 176 + (wg < 2 ? 64 : 0);
#pragma unroll
                for (int j = 0; j < 8; j++)
                    store_h(hrow, col0 + j * 8, g, acc[4 * j] * acc[32 + 4 * j], acc[4 * j + 1] * acc[33 + 4 * j],
                            acc[4 * j + 2] * acc[34 + 4 * j], acc[4 * j + 3] * acc[35 + 4 * j]);
            }
        }
        wg_publish(wg, C_H + rb, (tid & 127) == 0);

        if (wg == 0) {
            float acc[64];
            const uint64_t dH = mkdesc(sb + SM_DR, 16, 1024, 1), dW = mkdesc(sb + SM_DR + 16384, 16, 1024, 1);
            auto down_issue = [&](int st) {
                const uint32_t fb = bar + 8 * (B_DFULL + w), dst = sb + SM_DR + w * 24576;
                mbar_expect(fb, 24576);
                bulk_load(dst, g_H + ((size_t)rb * 22 + st) * 16384, 16384, fb);
                tma2d(dst + 16384, &tmD, fb, cg * 64, st * 64);
            };
            if (lane == 0) {
                cnt_wait(C_H + rb, (epoch + 1) * 32);
                down_issue(w);
            }
            __syncwarp();
#pragma unroll 1
            for (int s = 0; s < 22; s++) {
                mbar_wait(bar + 8 * (B_DFULL + (s & 3)), (s >> 2) & 1);
                const uint64_t a = dW + (s & 3) * 1536, b = dH + (s & 3) * 1536;
                wg_fence();
                wg_n128_ta(acc, a, b, s);
                wg_n128_ta(acc, a + 128, b + 2, 1);
                wg_n128_ta(acc, a + 256, b + 4, 1);
                wg_n128_ta(acc, a + 384, b + 6, 1);
                wg_commit();
                wg_wait<1>();
                if (s && lane == 0) {
                    mbar_arrive(bar + 8 * (B_DEMPTY + ((s - 1) & 3)));
                    if (((s - 1) & 3) == w && s + 3 < 22) {
                        mbar_wait(bar + 8 * (B_DEMPTY + w), ((s - 1) >> 2) & 1);
                        down_issue(s + 3);
                    }
                }
                __syncwarp();
            }
            wg_wait<0>();
            fence_regs(acc);
            float gv;
            asm volatile("ld.global.cg.f32 %0, [%1];" : "=f"(gv) : "l"(g_gate + rb * 128 + tid) : "memory");
            *(float*)(smem + SM_G + tid * 4) = gv;
            wg_bar(0);
            if (lane == 0) {
                mbar_expect(bar + 8 * B_WOFULL, 16384);
                tma2d(sb + SM_WO + w * 16384, &tmWO, bar + 8 * B_WOFULL, cg * 64, w * 128);
                tma2d(sb + SM_WO + w * 16384 + 8192, &tmWO, bar + 8 * B_WOFULL, cg * 64, w * 128 + 64);
            }
            __syncwarp();
#pragma unroll
            for (int j = 0; j < 16; j++) {
                const float2 gg = *(const float2*)(smem + SM_G + (8 * j + 2 * t) * 4);
                const float u0 = bf_round(1.f - gg.x), u1 = bf_round(1.f - gg.y);
                *(float4*)(smem + SM_BP + (j * 128 + tid) * 16) = make_float4(acc[4 * j] * u0, acc[4 * j + 1] * u1, acc[4 * j + 2] * u0, acc[4 * j + 3] * u1);
            }
            __syncwarp();
            if (lane == 0) mbar_arrive(bar + 8 * B_BREADY);
        }

        {
            const uint32_t one2 = 0x3C003C00u + (epoch == 0xFFFFFFFFu && sb == 1);
            const int nseg = wg == 0 ? 2 : 3;
#pragma unroll 1
            for (int sg = 0; sg < nseg; sg++) {
                int mt, c0 = 0, c1 = 16;
                if (wg == 0) { mt = sg; if (sg == 1) c1 = SPLIT0; }
                else if (sg == 0) { mt = 1; c0 = SPLIT0 + (wg - 1) * PIECE; c1 = c0 + PIECE; }
                else mt = 2 * wg + sg - 1;
                for (int j = c0 >> 1; j <= (c1 - 1) >> 1; j++) mbar_wait(bar + 8 * (B_KVFULL + j), 0);
                const int row = qq * 512 + mt * 64 + w * 16 + g;
                const uint8_t* qp = g_Q + ((size_t)head * SEQ + row) * 32 + t * 4;
                uint32_t qa[4];
                qa[0] = ld4(qp); qa[1] = ld4(qp + 256); qa[2] = ld4(qp + 16); qa[3] = ld4(qp + 256 + 16);
                float o[12];
#pragma unroll
                for (int i = 0; i < 12; i++) o[i] = 0.f;
                attn_fast(o, qa, sb, c0, c1, one2);
                o[9] = o[10];
                float* part = g_part + (size_t)blockIdx.x * 3 * 1280 + (tid & 127);
                if (wg != 0 && sg == 0) {
#pragma unroll
                    for (int i = 0; i < 10; i++) part[((wg - 1) * 10 + i) * 128] = o[i];
                    asm volatile("bar.arrive 5, 512;" ::: "memory");
                    continue;
                }
                if (wg == 0 && sg == 1) {
                    asm volatile("bar.sync 5, 512;" ::: "memory");
#pragma unroll
                    for (int i = 0; i < 30; i++) {
                        float v;
                        asm volatile("ld.global.cg.f32 %0, [%1];" : "=f"(v) : "l"(part + i * 128) : "memory");
                        o[i % 10] += v;
                    }
                }
                float i0 = 1.f / o[8], i1 = 1.f / o[9];
                {
                    float m0 = fmaxf(fmaxf(fabsf(o[0]), fabsf(o[1])), fmaxf(fabsf(o[4]), fabsf(o[5])));
                    float m1 = fmaxf(fmaxf(fabsf(o[2]), fabsf(o[3])), fmaxf(fabsf(o[6]), fabsf(o[7])));
                    const float chk = ((o[0] + o[1]) + (o[2] + o[3])) + ((o[4] + o[5]) + (o[6] + o[7]));
                    m0 = fmaxf(m0, __shfl_xor_sync(~0u, m0, 1)); m0 = fmaxf(m0, __shfl_xor_sync(~0u, m0, 2));
                    m1 = fmaxf(m1, __shfl_xor_sync(~0u, m1, 1)); m1 = fmaxf(m1, __shfl_xor_sync(~0u, m1, 2));
                    bool ok = o[8] >= 64.f && o[8] < 1e30f && o[9] >= 64.f && o[9] < 1e30f && fabsf(chk) < 1e37f &&
                              m0 * i0 >= 1.2207e-4f && m1 * i1 >= 1.2207e-4f;
                    if (wg_any(wg, !ok)) {
                        float tmp[10];
                        for (int j = 0; j < 8; j++) mbar_wait(bar + 8 * (B_KVFULL + j), 0);
                        attn_generic(tmp, qa[0], qa[1], qa[2], qa[3], sb, head);
#pragma unroll
                        for (int i = 0; i < 10; i++) o[i] = tmp[i];
                        i0 = 1.f / o[8]; i1 = 1.f / o[9];
                    }
                }
                uint8_t* op = g_O + ((size_t)(row >> 7) * 8 + (head >> 2)) * 16384 + (row & 127) * 128 +
                              ((((head & 3) * 2 + (t & 1)) ^ g) << 4) + (t >> 1) * 4;
                st4(op, pack_bf16(o[0] * i0, o[1] * i0));
                st4(op + 8, pack_bf16(o[4] * i0, o[5] * i0));
                st4(op + 1024, pack_bf16(o[2] * i1, o[3] * i1));
                st4(op + 1024 + 8, pack_bf16(o[6] * i1, o[7] * i1));
                wg_publish(wg, C_O + (row >> 7), (tid & 127) == 0);
            }
            if (lane == 0) mbar_arrive(bar + 8 * B_KVFREE);
        }

        if (wg == 1 || wg == 2) {
            const int hf = wg - 1, lt = tid & 127;
            float acc[32];
            const uint64_t dW = mkdesc(sb + SM_WO, 16, 1024, 1), dO = mkdesc(sb + SM_X + hf * 8192, 16, 1024, 1);
            if (lane == 0) {
                const int j = w * 2 + hf;
                mbar_wait(bar + 8 * B_KVFREE, 0);
                cnt_wait(C_O + rb, (epoch + 1) * 64);
                mbar_expect(bar + 8 * (B_OFULL + j), 16384);
                bulk_load(sb + SM_X + j * 16384, g_O + (size_t)rb * 131072 + j * 16384, 16384, bar + 8 * (B_OFULL + j));
            }
            __syncwarp();
            mbar_wait(bar + 8 * B_WOFULL, 0);
            mbar_wait(bar + 8 * B_BREADY, 0);
#pragma unroll 1
            for (int s = 0; s < 8; s++) {
                mbar_wait(bar + 8 * (B_OFULL + s), 0);
                const uint64_t a = dW + s * 512, b = dO + s * 1024;
                wg_fence();
                wg_n64_ta(acc, a, b, s);
                wg_n64_ta(acc, a + 128, b + 2, 1);
                wg_n64_ta(acc, a + 256, b + 4, 1);
                wg_n64_ta(acc, a + 384, b + 6, 1);
                wg_commit();
            }
            float4 bp[8];
            float2 gg[8];
#pragma unroll
            for (int j = 0; j < 8; j++) {
                bp[j] = *(const float4*)(smem + SM_BP + ((hf * 8 + j) * 128 + lt) * 16);
                gg[j] = *(const float2*)(smem + SM_G + (hf * 64 + 8 * j + 2 * t) * 4);
            }
            wg_wait<0>();
            fence_regs(acc);
            wg_bar(wg);
            const uint32_t stg = sb + SM_BP + hf * 16384;
#pragma unroll
            for (int j = 0; j < 8; j += 2) {
                const uint32_t r0 = pack_bf16(fmaf(acc[4 * j], gg[j].x, bp[j].x), fmaf(acc[4 * j + 1], gg[j].y, bp[j].y));
                const uint32_t r1 = pack_bf16(fmaf(acc[4 * j + 2], gg[j].x, bp[j].z), fmaf(acc[4 * j + 3], gg[j].y, bp[j].w));
                const uint32_t r2 = pack_bf16(fmaf(acc[4 * j + 4], gg[j + 1].x, bp[j + 1].x), fmaf(acc[4 * j + 5], gg[j + 1].y, bp[j + 1].y));
                const uint32_t r3 = pack_bf16(fmaf(acc[4 * j + 6], gg[j + 1].x, bp[j + 1].z), fmaf(acc[4 * j + 7], gg[j + 1].y, bp[j + 1].w));
                const int orow = 8 * (j + (lane >> 4)) + (lane & 7), ch = 2 * w + ((lane >> 3) & 1);
                asm volatile("stmatrix.sync.aligned.m8n8.x4.trans.shared.b16 [%0], {%1, %2, %3, %4};"
                             ::"r"(stg + orow * 128 + ((ch ^ (lane & 7)) << 4)), "r"(r0), "r"(r1), "r"(r2), "r"(r3) : "memory");
            }
            asm volatile("fence.proxy.async.shared::cta;" ::: "memory");
            wg_bar(wg);
            if (lt == 0) {
                asm volatile("cp.async.bulk.tensor.2d.global.shared::cta.bulk_group [%0, {%2, %3}], [%1];"
                             ::"l"(&tmOut), "r"(stg), "r"(cg * 64), "r"(rb * 128 + hf * 64) : "memory");
                asm volatile("cp.async.bulk.commit_group;" ::: "memory");
                asm volatile("cp.async.bulk.wait_group 0;" ::: "memory");
                if (blockIdx.x == 0 && hf == 0) asm volatile("st.relaxed.gpu.global.u32 [%0], %1;" ::"l"(&g_cnt[C_EPOCH * 32]), "r"(epoch + 1) : "memory");
            }
        }
    }
}

typedef CUresult (*EncodeFn)(CUtensorMap*, CUtensorMapDataType, cuuint32_t, void*, const cuuint64_t*, const cuuint64_t*,
                             const cuuint32_t*, const cuuint32_t*, CUtensorMapInterleave, CUtensorMapSwizzle,
                             CUtensorMapL2promotion, CUtensorMapFloatOOBfill);

void make_map(EncodeFn enc, CUtensorMap* m, const void* p, int rank, const cuuint64_t* dims, const cuuint64_t* strides, const cuuint32_t* box) {
    const cuuint32_t es[3] = {1, 1, 1};
    enc(m, CU_TENSOR_MAP_DATA_TYPE_BFLOAT16, rank, const_cast<void*>(p), dims, strides, box, es, CU_TENSOR_MAP_INTERLEAVE_NONE,
        CU_TENSOR_MAP_SWIZZLE_128B, CU_TENSOR_MAP_L2_PROMOTION_L2_128B, CU_TENSOR_MAP_FLOAT_OOB_FILL_NONE);
}
void make_map2(EncodeFn enc, CUtensorMap* m, const void* p, uint64_t cols, uint64_t rows, uint32_t bc, uint32_t br) {
    const cuuint64_t d[2] = {cols, rows}, s[1] = {cols * 2};
    const cuuint32_t b[2] = {bc, br};
    make_map(enc, m, p, 2, d, s, b);
}

}

extern "C" void kernel_launch(void* const* d_in, const int* in_sizes, int n_in, void* d_out, int out_size) {
    (void)in_sizes; (void)n_in; (void)out_size;
    void* fn = nullptr;
    cudaDriverEntryPointQueryResult qr;
    cudaGetDriverEntryPoint("cuTensorMapEncodeTiled", &fn, cudaEnableDefault, &qr);
    EncodeFn enc = (EncodeFn)fn;
    CUtensorMap tmX, tmQKV, tmG, tmU, tmD, tmWO, tmOut;
    make_map2(enc, &tmX, d_in[0], 512, 2048, 64, 128);
    make_map2(enc, &tmQKV, d_in[1], 1536, 512, 64, 32);
    make_map2(enc, &tmG, d_in[4], 1376, 512, 64, 32);
    make_map2(enc, &tmU, d_in[5], 1376, 512, 64, 32);
    make_map2(enc, &tmD, d_in[6], 512, 1376, 64, 64);
    make_map2(enc, &tmWO, d_in[2], 512, 512, 64, 64);
    make_map2(enc, &tmOut, d_out, 512, 2048, 64, 64);
    cudaFuncSetAttribute(fused_kernel, cudaFuncAttributeMaxDynamicSharedMemorySize, SM_TOTAL);
    fused_kernel<<<NCTA, NTHREADS, SM_TOTAL>>>(tmX, tmQKV, tmG, tmU, tmD, tmWO, tmOut, (const uint4*)d_in[0], (const uint4*)d_in[7]);
}
```

```cpp
#include <cuda_runtime.h>
#include <cuda.h>
#include <cuda_bf16.h>
#include <stdint.h>

namespace {

constexpr int SEQ = 2048;
constexpr int NCTA = 128;
constexpr int NHELP = 4;
constexpr int NTHREADS = 640;

constexpr uint32_t SM_X = 0;
constexpr uint32_t SM_WA = 131072, SM_WB = 131072 + 49152;
__host__ __device__ constexpr uint32_t wa_off(int j) { return SM_WA + (j % 3) * 16384; }
__host__ __device__ constexpr uint32_t wb_off(int j) { return SM_WB + (j % 3) * 16384; }
constexpr uint32_t SM_DR = 131072;
constexpr uint32_t SM_BP = 131072;
constexpr uint32_t SM_WO = 131072 + 32768;
constexpr uint32_t SM_ONES = 229376;
constexpr uint32_t SM_G = SM_ONES + 512;
constexpr uint32_t SM_BAR = SM_G + 512;
constexpr uint32_t SM_GW = SM_BAR + 1024;
constexpr uint32_t SM_TOTAL = SM_GW + 1024;
enum {
    B_XFULL = 0, B_AFULL = 8, B_BFULL = 24, B_AEMPTY = 40, B_BEMPTY = 56,
    B_QKVW = 72, B_HW, B_OWH, B_KVFREE,
    B_QKVOK = 80, B_HOK, B_POK, B_WOFULL, B_OFULL  , B_KVFULL = 96,
    B_DFULL = 104,
    B_DEMPTY = 112, B_BREADY = 116, B_OW0, B_COUNT = 120
};

constexpr int PC1 = 3, PC2 = 3, PC3 = 4, HU = 2;
constexpr int SPA = 4, SPB = 2;

__device__ __align__(1024) uint8_t g_Q[32 * SEQ * 32];
__device__ __align__(1024) uint8_t g_KV[32 * 16 * 8192];
__device__ __align__(1024) uint8_t g_H[16 * 22 * 16384];
__device__ __align__(1024) uint8_t g_O[32 * 65536];
__device__ __align__(1024) float g_gate[SEQ];
__device__ __align__(1024) float g_part[NCTA * 4 * 10 * 128];
__device__ __align__(1024) unsigned g_cnt[96 * 32];
constexpr int C_QKV = 0, C_H = 8, C_O = 24, C_EPOCH = 40, C_P = 48, C_O0 = 80;

__device__ __forceinline__ void wg_n128_tb64(float (&d)[64], uint32_t da, uint32_t db, int sd) {
    asm volatile("{.reg .pred p; .reg .b64 da, db; setp.ne.b32 p, %66, 0; mov.b64 da, {%64, 0x40000040}; mov.b64 db, {%65, 0x80000020};\n"
        "wgmma.mma_async.sync.aligned.m64n128k16.f32.bf16.bf16 {%0, %1, %2, %3, %4, %5, %6, %7, %8, %9, %10, %11, %12, %13, %14, %15, %16, %17, %18, %19, %20, %21, %22, %23, %24, %25, %26, %27, %28, %29, %30, %31, %32, %33, %34, %35, %36, %37, %38, %39, %40, %41, %42, %43, %44, %45, %46, %47, %48, %49, %50, %51, %52, %53, %54, %55, %56, %57, %58, %59, %60, %61, %62, %63}, da, db, p, 1, 1, 0, 1;}"
        : "+f"(d[0]), "+f"(d[1]), "+f"(d[2]), "+f"(d[3]), "+f"(d[4]), "+f"(d[5]), "+f"(d[6]), "+f"(d[7]), "+f"(d[8]), "+f"(d[9]), "+f"(d[10]), "+f"(d[11]), "+f"(d[12]), "+f"(d[13]), "+f"(d[14]), "+f"(d[15]), "+f"(d[16]), "+f"(d[17]), "+f"(d[18]), "+f"(d[19]), "+f"(d[20]), "+f"(d[21]), "+f"(d[22]), "+f"(d[23]), "+f"(d[24]), "+f"(d[25]), "+f"(d[26]), "+f"(d[27]), "+f"(d[28]), "+f"(d[29]), "+f"(d[30]), "+f"(d[31]), "+f"(d[32]), "+f"(d[33]), "+f"(d[34]), "+f"(d[35]), "+f"(d[36]), "+f"(d[37]), "+f"(d[38]), "+f"(d[39]), "+f"(d[40]), "+f"(d[41]), "+f"(d[42]), "+f"(d[43]), "+f"(d[44]), "+f"(d[45]), "+f"(d[46]), "+f"(d[47]), "+f"(d[48]), "+f"(d[49]), "+f"(d[50]), "+f"(d[51]), "+f"(d[52]), "+f"(d[53]), "+f"(d[54]), "+f"(d[55]), "+f"(d[56]), "+f"(d[57]), "+f"(d[58]), "+f"(d[59]), "+f"(d[60]), "+f"(d[61]), "+f"(d[62]), "+f"(d[63])
        : "r"(da), "r"(db), "r"(sd));
}
__device__ __forceinline__ void wg_n128_tb(float (&d)[64], uint32_t da, uint32_t db, int sd) {
    asm volatile("{.reg .pred p; .reg .b64 da, db; setp.ne.b32 p, %66, 0; mov.b64 da, {%64, 0x40000040}; mov.b64 db, {%65, 0x40000040};\n"
        "wgmma.mma_async.sync.aligned.m64n128k16.f32.bf16.bf16 {%0, %1, %2, %3, %4, %5, %6, %7, %8, %9, %10, %11, %12, %13, %14, %15, %16, %17, %18, %19, %20, %21, %22, %23, %24, %25, %26, %27, %28, %29, %30, %31, %32, %33, %34, %35, %36, %37, %38, %39, %40, %41, %42, %43, %44, %45, %46, %47, %48, %49, %50, %51, %52, %53, %54, %55, %56, %57, %58, %59, %60, %61, %62, %63}, da, db, p, 1, 1, 0, 1;}"
        : "+f"(d[0]), "+f"(d[1]), "+f"(d[2]), "+f"(d[3]), "+f"(d[4]), "+f"(d[5]), "+f"(d[6]), "+f"(d[7]), "+f"(d[8]), "+f"(d[9]), "+f"(d[10]), "+f"(d[11]), "+f"(d[12]), "+f"(d[13]), "+f"(d[14]), "+f"(d[15]), "+f"(d[16]), "+f"(d[17]), "+f"(d[18]), "+f"(d[19]), "+f"(d[20]), "+f"(d[21]), "+f"(d[22]), "+f"(d[23]), "+f"(d[24]), "+f"(d[25]), "+f"(d[26]), "+f"(d[27]), "+f"(d[28]), "+f"(d[29]), "+f"(d[30]), "+f"(d[31]), "+f"(d[32]), "+f"(d[33]), "+f"(d[34]), "+f"(d[35]), "+f"(d[36]), "+f"(d[37]), "+f"(d[38]), "+f"(d[39]), "+f"(d[40]), "+f"(d[41]), "+f"(d[42]), "+f"(d[43]), "+f"(d[44]), "+f"(d[45]), "+f"(d[46]), "+f"(d[47]), "+f"(d[48]), "+f"(d[49]), "+f"(d[50]), "+f"(d[51]), "+f"(d[52]), "+f"(d[53]), "+f"(d[54]), "+f"(d[55]), "+f"(d[56]), "+f"(d[57]), "+f"(d[58]), "+f"(d[59]), "+f"(d[60]), "+f"(d[61]), "+f"(d[62]), "+f"(d[63])
        : "r"(da), "r"(db), "r"(sd));
}
__device__ __forceinline__ void wg_n64_tb64(float (&d)[32], uint32_t da, uint32_t db, int sd) {
    asm volatile("{.reg .pred p; .reg .b64 da, db; setp.ne.b32 p, %34, 0; mov.b64 da, {%32, 0x40000040}; mov.b64 db, {%33, 0x80000020};\n"
        "wgmma.mma_async.sync.aligned.m64n64k16.f32.bf16.bf16 {%0, %1, %2, %3, %4, %5, %6, %7, %8, %9, %10, %11, %12, %13, %14, %15, %16, %17, %18, %19, %20, %21, %22, %23, %24, %25, %26, %27, %28, %29, %30, %31}, da, db, p, 1, 1, 0, 1;}"
        : "+f"(d[0]), "+f"(d[1]), "+f"(d[2]), "+f"(d[3]), "+f"(d[4]), "+f"(d[5]), "+f"(d[6]), "+f"(d[7]), "+f"(d[8]), "+f"(d[9]), "+f"(d[10]), "+f"(d[11]), "+f"(d[12]), "+f"(d[13]), "+f"(d[14]), "+f"(d[15]), "+f"(d[16]), "+f"(d[17]), "+f"(d[18]), "+f"(d[19]), "+f"(d[20]), "+f"(d[21]), "+f"(d[22]), "+f"(d[23]), "+f"(d[24]), "+f"(d[25]), "+f"(d[26]), "+f"(d[27]), "+f"(d[28]), "+f"(d[29]), "+f"(d[30]), "+f"(d[31])
        : "r"(da), "r"(db), "r"(sd));
}
__device__ __forceinline__ void wg_n128_ta(float (&d)[64], uint32_t da, uint32_t db, int sd) {
    asm volatile("{.reg .pred p; .reg .b64 da, db; setp.ne.b32 p, %66, 0; mov.b64 da, {%64, 0x40000040}; mov.b64 db, {%65, 0x00000008};\n"
        "wgmma.mma_async.sync.aligned.m64n128k16.f32.bf16.bf16 {%0, %1, %2, %3, %4, %5, %6, %7, %8, %9, %10, %11, %12, %13, %14, %15, %16, %17, %18, %19, %20, %21, %22, %23, %24, %25, %26, %27, %28, %29, %30, %31, %32, %33, %34, %35, %36, %37, %38, %39, %40, %41, %42, %43, %44, %45, %46, %47, %48, %49, %50, %51, %52, %53, %54, %55, %56, %57, %58, %59, %60, %61, %62, %63}, da, db, p, 1, 1, 1, 0;}"
        : "+f"(d[0]), "+f"(d[1]), "+f"(d[2]), "+f"(d[3]), "+f"(d[4]), "+f"(d[5]), "+f"(d[6]), "+f"(d[7]), "+f"(d[8]), "+f"(d[9]), "+f"(d[10]), "+f"(d[11]), "+f"(d[12]), "+f"(d[13]), "+f"(d[14]), "+f"(d[15]), "+f"(d[16]), "+f"(d[17]), "+f"(d[18]), "+f"(d[19]), "+f"(d[20]), "+f"(d[21]), "+f"(d[22]), "+f"(d[23]), "+f"(d[24]), "+f"(d[25]), "+f"(d[26]), "+f"(d[27]), "+f"(d[28]), "+f"(d[29]), "+f"(d[30]), "+f"(d[31]), "+f"(d[32]), "+f"(d[33]), "+f"(d[34]), "+f"(d[35]), "+f"(d[36]), "+f"(d[37]), "+f"(d[38]), "+f"(d[39]), "+f"(d[40]), "+f"(d[41]), "+f"(d[42]), "+f"(d[43]), "+f"(d[44]), "+f"(d[45]), "+f"(d[46]), "+f"(d[47]), "+f"(d[48]), "+f"(d[49]), "+f"(d[50]), "+f"(d[51]), "+f"(d[52]), "+f"(d[53]), "+f"(d[54]), "+f"(d[55]), "+f"(d[56]), "+f"(d[57]), "+f"(d[58]), "+f"(d[59]), "+f"(d[60]), "+f"(d[61]), "+f"(d[62]), "+f"(d[63])
        : "r"(da), "r"(db), "r"(sd));
}
__device__ __forceinline__ void wg_n64_ta(float (&d)[32], uint32_t da, uint32_t db, int sd) {
    asm volatile("{.reg .pred p; .reg .b64 da, db; setp.ne.b32 p, %34, 0; mov.b64 da, {%32, 0x40000040}; mov.b64 db, {%33, 0x00000008};\n"
        "wgmma.mma_async.sync.aligned.m64n64k16.f32.bf16.bf16 {%0, %1, %2, %3, %4, %5, %6, %7, %8, %9, %10, %11, %12, %13, %14, %15, %16, %17, %18, %19, %20, %21, %22, %23, %24, %25, %26, %27, %28, %29, %30, %31}, da, db, p, 1, 1, 1, 0;}"
        : "+f"(d[0]), "+f"(d[1]), "+f"(d[2]), "+f"(d[3]), "+f"(d[4]), "+f"(d[5]), "+f"(d[6]), "+f"(d[7]), "+f"(d[8]), "+f"(d[9]), "+f"(d[10]), "+f"(d[11]), "+f"(d[12]), "+f"(d[13]), "+f"(d[14]), "+f"(d[15]), "+f"(d[16]), "+f"(d[17]), "+f"(d[18]), "+f"(d[19]), "+f"(d[20]), "+f"(d[21]), "+f"(d[22]), "+f"(d[23]), "+f"(d[24]), "+f"(d[25]), "+f"(d[26]), "+f"(d[27]), "+f"(d[28]), "+f"(d[29]), "+f"(d[30]), "+f"(d[31])
        : "r"(da), "r"(db), "r"(sd));
}
__device__ __forceinline__ void wg_qk_n64(float (&d)[32], const uint32_t (&a)[4], uint64_t db) {
    asm volatile("wgmma.mma_async.sync.aligned.m64n64k16.f32.bf16.bf16 {%0, %1, %2, %3, %4, %5, %6, %7, %8, %9, %10, %11, %12, %13, %14, %15, %16, %17, %18, %19, %20, %21, %22, %23, %24, %25, %26, %27, %28, %29, %30, %31}, {%32,%33,%34,%35}, %36, 0, 1, 1, 0;"
        : "=f"(d[0]), "=f"(d[1]), "=f"(d[2]), "=f"(d[3]), "=f"(d[4]), "=f"(d[5]), "=f"(d[6]), "=f"(d[7]), "=f"(d[8]), "=f"(d[9]), "=f"(d[10]), "=f"(d[11]), "=f"(d[12]), "=f"(d[13]), "=f"(d[14]), "=f"(d[15]), "=f"(d[16]), "=f"(d[17]), "=f"(d[18]), "=f"(d[19]), "=f"(d[20]), "=f"(d[21]), "=f"(d[22]), "=f"(d[23]), "=f"(d[24]), "=f"(d[25]), "=f"(d[26]), "=f"(d[27]), "=f"(d[28]), "=f"(d[29]), "=f"(d[30]), "=f"(d[31])
        : "r"(a[0]), "r"(a[1]), "r"(a[2]), "r"(a[3]), "l"(db));
}
__device__ __forceinline__ void wg_pv_n24(float (&d)[12], uint32_t a0, uint32_t a1, uint32_t a2, uint32_t a3, uint64_t db) {
    asm volatile("wgmma.mma_async.sync.aligned.m64n24k16.f32.f16.f16 {%0, %1, %2, %3, %4, %5, %6, %7, %8, %9, %10, %11}, {%12,%13,%14,%15}, %16, 1, 1, 1, 1;"
        : "+f"(d[0]), "+f"(d[1]), "+f"(d[2]), "+f"(d[3]), "+f"(d[4]), "+f"(d[5]), "+f"(d[6]), "+f"(d[7]), "+f"(d[8]), "+f"(d[9]), "+f"(d[10]), "+f"(d[11])
        : "r"(a0), "r"(a1), "r"(a2), "r"(a3), "l"(db));
}

__device__ __forceinline__ void wg_fence() { asm volatile("wgmma.fence.sync.aligned;" ::: "memory"); }
__device__ __forceinline__ void wg_commit() { asm volatile("wgmma.commit_group.sync.aligned;" ::: "memory"); }
template <int N> __device__ __forceinline__ void wg_wait() { asm volatile("wgmma.wait_group.sync.aligned %0;" ::"n"(N) : "memory"); }
template <int N> __device__ __forceinline__ void fence_regs(float (&d)[N]) {
#pragma unroll
    for (int i = 0; i < N; i++) asm volatile("" : "+f"(d[i])::"memory");
}
__device__ __forceinline__ uint32_t desc_lo(uint32_t addr, uint32_t lbo) { return ((addr & 0x3FFFF) >> 4) | ((lbo >> 4) << 16); }
__device__ __forceinline__ void mbar_init(uint32_t a, uint32_t c) { asm volatile("mbarrier.init.shared::cta.b64 [%0], %1;" ::"r"(a), "r"(c) : "memory"); }
__device__ __forceinline__ void mbar_expect(uint32_t a, uint32_t b) { asm volatile("mbarrier.arrive.expect_tx.shared::cta.b64 _, [%0], %1;" ::"r"(a), "r"(b) : "memory"); }
__device__ __forceinline__ void mbar_arrive_lane0(uint32_t a, int lane) {
    asm volatile("{.reg .pred p; setp.eq.s32 p, %1, 0; @p mbarrier.arrive.shared::cta.b64 _, [%0];}" ::"r"(a), "r"(lane) : "memory");
}
__device__ __forceinline__ void mbar_arrive(uint32_t a) { asm volatile("mbarrier.arrive.shared::cta.b64 _, [%0];" ::"r"(a) : "memory"); }
__device__ __forceinline__ void mbar_wait(uint32_t a, uint32_t ph) {
    asm volatile("{.reg .pred p; .reg .u32 t0, t1;\n"
                 "mbarrier.try_wait.parity.shared::cta.b64 p, [%0], %1;\n"
                 "@p bra.uni WD%=;\n"
                 "mov.u32 t0, %%clock;\n"
                 "WL%=:\n"
                 "mbarrier.try_wait.parity.shared::cta.b64 p, [%0], %1;\n"
                 "@p bra.uni WD%=;\n"
                 "mov.u32 t1, %%clock;\n"
                 "sub.u32 t1, t1, t0;\n"
                 "setp.lt.u32 p, t1, 0x10000000;\n"
                 "@p bra.uni WL%=;\n"
                 "WD%=:}" ::"r"(a), "r"(ph) : "memory");
}
__device__ __forceinline__ void tma2d(uint32_t dst, const CUtensorMap* tm, uint32_t bar, int x, int y) {
    asm volatile("cp.async.bulk.tensor.2d.shared::cluster.global.mbarrier::complete_tx::bytes [%0], [%1, {%3, %4}], [%2];"
                 ::"r"(dst), "l"(tm), "r"(bar), "r"(x), "r"(y) : "memory");
}
__device__ __forceinline__ void tma3d(uint32_t dst, const CUtensorMap* tm, uint32_t bar, int x, int y, int z) {
    asm volatile("cp.async.bulk.tensor.3d.shared::cluster.global.mbarrier::complete_tx::bytes [%0], [%1, {%3, %4, %5}], [%2];"
                 ::"r"(dst), "l"(tm), "r"(bar), "r"(x), "r"(y), "r"(z) : "memory");
}
__device__ __forceinline__ void bulk_load(uint32_t dst, const void* src, uint32_t bytes, uint32_t bar) {
    asm volatile("cp.async.bulk.shared::cluster.global.mbarrier::complete_tx::bytes [%0], [%1], %2, [%3];"
                 ::"r"(dst), "l"(src), "r"(bytes), "r"(bar) : "memory");
}
__device__ __forceinline__ void l2_prefetch(const void* p) { asm volatile("prefetch.global.L2 [%0];" ::"l"(p)); }
__device__ __forceinline__ int fresh_tid() {
    int v;
    asm volatile("mov.u32 %0, %%tid.x;" : "=r"(v));
    return v;
}
__device__ __forceinline__ int uni(int v) { return __reduce_max_sync(~0u, v); }
__device__ __forceinline__ void proxy_fence() { asm volatile("fence.proxy.async.global;" ::: "memory"); }
__device__ __forceinline__ uint32_t mbar_probe(uint32_t a, uint32_t ph) {
    uint32_t ok;
    asm volatile("{.reg .pred p; mbarrier.test_wait.parity.shared::cta.b64 p, [%1], %2; selp.u32 %0, 1, 0, p;}" : "=r"(ok) : "r"(a), "r"(ph) : "memory");
    return ok;
}
__device__ __forceinline__ void wg_bar(int wg) { asm volatile("bar.sync %0, 128;" ::"r"(wg + 1) : "memory"); }
__device__ __forceinline__ bool wg_any(int wg, bool v) {
    uint32_t r;
    asm volatile("{.reg .pred p, q; setp.ne.u32 p, %2, 0; bar.red.or.pred q, %1, 128, p; selp.u32 %0, 1, 0, q;}" : "=r"(r) : "r"(wg + 1), "r"((uint32_t)v) : "memory");
    return r;
}
__device__ __forceinline__ void cnt_signal(int idx) {
    asm volatile("red.release.gpu.global.add.u32 [%0], 1;" ::"l"(&g_cnt[idx * 32]) : "memory");
}
__device__ __forceinline__ unsigned cnt_load(int idx) {
    unsigned v;
    asm volatile("ld.relaxed.gpu.global.u32 %0, [%1];" : "=r"(v) : "l"(&g_cnt[idx * 32]) : "memory");
    return v;
}
__device__ __forceinline__ void cnt_wait(int idx, unsigned target) {
    unsigned a = cnt_load(idx);
    __nanosleep(100);
    unsigned b = cnt_load(idx);
    __nanosleep(100);
    unsigned c = cnt_load(idx);
    for (uint32_t n = 0; n < (1u << 20); n++) {
        if ((int)(a - target) >= 0) break;
        a = cnt_load(idx);
        if ((int)(b - target) >= 0) break;
        b = cnt_load(idx);
        if ((int)(c - target) >= 0) break;
        c = cnt_load(idx);
    }
    asm volatile("fence.acquire.gpu;" ::: "memory");
}
__device__ __forceinline__ void cnt_wait_slow(int idx, unsigned target) {
    for (uint32_t n = 0; n < (1u << 20) && (int)(cnt_load(idx) - target) < 0; n++) __nanosleep(500);
    asm volatile("fence.acquire.gpu;" ::: "memory");
}
__device__ __forceinline__ float ex2(float x) { float y; asm("ex2.approx.ftz.f32 %0, %1;" : "=f"(y) : "f"(x)); return y; }
__device__ __forceinline__ uint32_t pack_bf16(float lo, float hi) { uint32_t y; asm("cvt.rn.bf16x2.f32 %0, %1, %2;" : "=r"(y) : "f"(hi), "f"(lo)); return y; }
__device__ __forceinline__ uint32_t pack_f16(float lo, float hi) { uint32_t y; asm("cvt.rn.f16x2.f32 %0, %1, %2;" : "=r"(y) : "f"(hi), "f"(lo)); return y; }
__device__ __forceinline__ uint32_t hfma2(uint32_t a, uint32_t b, uint32_t c) { uint32_t y; asm("fma.rn.f16x2 %0, %1, %2, %3;" : "=r"(y) : "r"(a), "r"(b), "r"(c)); return y; }
__device__ __forceinline__ uint32_t bmul2(uint32_t a, uint32_t b) { uint32_t y; asm("mul.rn.bf16x2 %0, %1, %2;" : "=r"(y) : "r"(a), "r"(b)); return y; }
__device__ __forceinline__ float bf_lo(uint32_t v) { return __uint_as_float(v << 16); }
__device__ __forceinline__ float bf_hi(uint32_t v) { return __uint_as_float(v & 0xFFFF0000u); }
__device__ __forceinline__ float bf_round(float v) { return bf_lo(pack_bf16(v, 0.f)); }
__device__ __forceinline__ void st8(void* p, uint32_t a, uint32_t b) { asm volatile("st.global.v2.u32 [%0], {%1, %2};" ::"l"(p), "r"(a), "r"(b) : "memory"); }
__device__ __forceinline__ void st4(void* p, uint32_t a) { asm volatile("st.global.u32 [%0], %1;" ::"l"(p), "r"(a) : "memory"); }
__device__ __forceinline__ uint32_t ld4(const void* p) { uint32_t v; asm volatile("ld.global.cg.u32 %0, [%1];" : "=r"(v) : "l"(p) : "memory"); return v; }

__device__ __forceinline__ uint32_t exp2_pair_fma(float x0, float x1, uint32_t one2) {
    float t0, t1;
    asm("fma.rn.f32 %0, %1, 0f00000400, 0f00003C00;" : "=f"(t0) : "f"(x0));
    asm("fma.rn.f32 %0, %1, 0f00000400, 0f00003C00;" : "=f"(t1) : "f"(x1));
    uint32_t u, g;
    asm("cvt.pack.sat.s16.s32 %0, %1, %2;" : "=r"(u) : "r"(__float_as_int(t1)), "r"(__float_as_int(t0)));
    asm("lop3.b32 %0, %1, 0x03FF03FF, %2, 0xEA;" : "=r"(g) : "r"(u), "r"(one2));
    uint32_t p = hfma2(0x2d012d01u, g, 0xa082a082u);
    p = hfma2(p, g, 0x37ab37abu);
    p = hfma2(p, g, 0x37383738u);
    return p + u - g;
}
constexpr uint32_t POLY_MASK = 0xFBC0;
__device__ __forceinline__ void softmax_tile(const float (&s)[32], uint32_t (&p)[16], uint32_t one2) {
#pragma unroll
    for (int i = 0; i < 16; i++) {
        if ((POLY_MASK >> i) & 1) p[i] = exp2_pair_fma(s[2 * i], s[2 * i + 1], one2);
        else p[i] = pack_f16(ex2(s[2 * i]), ex2(s[2 * i + 1]));
    }
}
constexpr uint64_t VSTEP16 = 32ull - (32ull << 16);
__device__ __forceinline__ void pv_tile(float (&o)[12], const uint32_t (&p)[16], uint64_t v) {
#pragma unroll
    for (int kk = 0; kk < 4; kk++) wg_pv_n24(o, p[4 * kk], p[4 * kk + 1], p[4 * kk + 2], p[4 * kk + 3], v + kk * VSTEP16);
}

constexpr uint64_t KV_HI = (uint64_t)0xC0000010u << 32;
constexpr uint64_t KT = 128, KU = 512, VT = 4 * VSTEP16, VU = 512ull - (512ull << 16);
#define ATTN_BEGIN                                                                                     \
    float s[32];                                                                                       \
    uint32_t p0[16], p1[16];                                                                           \
    __syncwarp();                    \
    fence_regs(o);                                                                                     \
    wg_fence();                                                                                        \
    wg_qk_n64(s, qa, k);                                                                               \
    wg_commit();                                                                                       \
    wg_wait<0>();                                                                                      \
    softmax_tile(s, p0, one2);
#define ATTN_UNIT                                                                                      \
    wg_fence();                                                                                        \
    wg_qk_n64(s, qa, k + KT);                                                                          \
    wg_commit();                                                                                       \
    pv_tile(o, p0, v);                                                                                 \
    wg_commit();                                                                                       \
    wg_wait<1>();                                                                                      \
    softmax_tile(s, p1, one2);                                                                         \
    wg_fence();                                                                                        \
    wg_qk_n64(s, qa, k + KU);                                                                          \
    wg_commit();                                                                                       \
    pv_tile(o, p1, v + VT);                                                                            \
    wg_commit();                                                                                       \
    wg_wait<1>();                                                                                      \
    softmax_tile(s, p0, one2);
#define ATTN_END                                                                                       \
    wg_fence();                                                                                        \
    wg_qk_n64(s, qa, k + KT);                                                                          \
    wg_commit();                                                                                       \
    pv_tile(o, p0, v);                                                                                 \
    wg_commit();                                                                                       \
    wg_wait<1>();                                                                                      \
    softmax_tile(s, p1, one2);                                                                         \
    wg_fence();                                                                                        \
    pv_tile(o, p1, v + VT);                                                                            \
    wg_commit();                                                                                       \
    wg_wait<0>();                                                                                      \
    fence_regs(o);

__device__ __forceinline__ void attn_range(float (&o)[12], const uint32_t (&qa)[4], uint32_t sb, uint32_t one2, int c0, int c1) {
    c0 = uni(c0); c1 = uni(c1);
    const uint32_t ka = sb + SM_X + c0 * 8192;
    uint64_t k = KV_HI | desc_lo(ka, 16), v = KV_HI | desc_lo(ka + 4096, sb + SM_ONES - ka - 4096);
    ATTN_BEGIN
#pragma unroll 1
    for (int c = c0 + 2; c < c1; c += 2) {
        const uint64_t kk = k, vv = v;
        { const uint64_t k = kk, v = vv; ATTN_UNIT }
        { const uint64_t k = kk + KU, v = vv + VU; ATTN_UNIT }
        k += 2 * KU; v += 2 * VU;
    }
    if (!((c1 - c0) & 1)) {
        ATTN_UNIT
        k += KU; v += VU;
    }
    ATTN_END
}

__device__ __forceinline__ void mma_bf16(float (&d)[4], const uint32_t (&a)[4], uint32_t b0, uint32_t b1) {
    asm volatile("mma.sync.aligned.m16n8k16.row.col.f32.bf16.bf16.f32 {%0,%1,%2,%3}, {%4,%5,%6,%7}, {%8,%9}, {%0,%1,%2,%3};"
                 : "+f"(d[0]), "+f"(d[1]), "+f"(d[2]), "+f"(d[3]) : "r"(a[0]), "r"(a[1]), "r"(a[2]), "r"(a[3]), "r"(b0), "r"(b1));
}
__device__ __forceinline__ uint32_t movm(uint32_t a) { uint32_t d; asm volatile("movmatrix.sync.aligned.m8n8.trans.b16 %0, %1;" : "=r"(d) : "r"(a)); return d; }

__device__ __noinline__ void attn_generic(float* o_out, uint32_t q0, uint32_t q1, uint32_t q2, uint32_t q3, int head,
                                          const uint8_t* __restrict__ x, const uint8_t* __restrict__ wqkv) {
    const int lane = threadIdx.x & 31, g = lane >> 2, t = lane & 3;
    const uint32_t qa[4] = {q0, q1, q2, q3};
    float oa[4] = {0, 0, 0, 0}, ob[4] = {0, 0, 0, 0};
    float m0 = -INFINITY, m1 = -INFINITY, l0 = 0.f, l1 = 0.f;
    const uint8_t* wv = wqkv + g * 3072 + (1024 + head * 16 + (t & 1) * 8 + (t >> 1) * 2) * 2;
#pragma unroll 1
    for (int kb = 0; kb < SEQ / 16; kb++) {
        float sa[4] = {0, 0, 0, 0}, sc[4] = {0, 0, 0, 0};
#pragma unroll
        for (int h = 0; h < 2; h++) {
            int key = kb * 16 + h * 8 + g, kl = key & 127, sw = (kl >> 2) & 1;
            const uint8_t* kr = g_KV + (size_t)head * 131072 + (key >> 7) * 8192 + kl * 32 + t * 4;
            const uint32_t b0 = ld4(kr + sw * 16), b1 = ld4(kr + (sw ^ 1) * 16);
            if (h == 0) mma_bf16(sa, qa, b0, b1); else mma_bf16(sc, qa, b0, b1);
        }
        float va[4] = {0, 0, 0, 0}, vb[4] = {0, 0, 0, 0};
        const uint8_t* xr = x + (size_t)(kb * 16 + g) * 1024 + t * 4;
#pragma unroll 4
        for (int ks = 0; ks < 32; ks++) {
            const uint32_t xa[4] = {__ldg((const uint32_t*)(xr + ks * 32)), __ldg((const uint32_t*)(xr + 8192 + ks * 32)),
                                    __ldg((const uint32_t*)(xr + ks * 32 + 16)), __ldg((const uint32_t*)(xr + 8192 + ks * 32 + 16))};
            const uint8_t* wr = wv + ks * 16 * 3072;
            mma_bf16(va, xa, movm(__ldg((const uint32_t*)wr)), movm(__ldg((const uint32_t*)(wr + 8 * 3072))));
            mma_bf16(vb, xa, movm(__ldg((const uint32_t*)(wr + 8))), movm(__ldg((const uint32_t*)(wr + 8 * 3072 + 8))));
        }
        float x0 = fmaxf(fmaxf(sa[0], sa[1]), fmaxf(sc[0], sc[1])), x1 = fmaxf(fmaxf(sa[2], sa[3]), fmaxf(sc[2], sc[3]));
        x0 = fmaxf(x0, __shfl_xor_sync(~0u, x0, 1)); x0 = fmaxf(x0, __shfl_xor_sync(~0u, x0, 2));
        x1 = fmaxf(x1, __shfl_xor_sync(~0u, x1, 1)); x1 = fmaxf(x1, __shfl_xor_sync(~0u, x1, 2));
        float n0 = fmaxf(m0, x0), n1 = fmaxf(m1, x1);
        float a0 = ex2(m0 - n0), a1 = ex2(m1 - n1);
        m0 = n0; m1 = n1;
        float e0 = ex2(sa[0] - n0), e1 = ex2(sa[1] - n0), e2 = ex2(sa[2] - n1), e3 = ex2(sa[3] - n1);
        float f0 = ex2(sc[0] - n0), f1 = ex2(sc[1] - n0), f2 = ex2(sc[2] - n1), f3 = ex2(sc[3] - n1);
        l0 = l0 * a0 + (e0 + e1) + (f0 + f1);
        l1 = l1 * a1 + (e2 + e3) + (f2 + f3);
        oa[0] *= a0; oa[1] *= a0; oa[2] *= a1; oa[3] *= a1;
        ob[0] *= a0; ob[1] *= a0; ob[2] *= a1; ob[3] *= a1;
        const uint32_t pa[4] = {pack_bf16(e0, e1), pack_bf16(e2, e3), pack_bf16(f0, f1), pack_bf16(f2, f3)};
        mma_bf16(oa, pa, movm(pack_bf16(va[0], va[1])), movm(pack_bf16(va[2], va[3])));
        mma_bf16(ob, pa, movm(pack_bf16(vb[0], vb[1])), movm(pack_bf16(vb[2], vb[3])));
    }
    l0 += __shfl_xor_sync(~0u, l0, 1); l0 += __shfl_xor_sync(~0u, l0, 2);
    l1 += __shfl_xor_sync(~0u, l1, 1); l1 += __shfl_xor_sync(~0u, l1, 2);
    o_out[0] = oa[0]; o_out[1] = oa[1]; o_out[2] = oa[2]; o_out[3] = oa[3];
    o_out[4] = ob[0]; o_out[5] = ob[1]; o_out[6] = ob[2]; o_out[7] = ob[3];
    o_out[8] = l0; o_out[9] = l1;
}

__device__ __forceinline__ void store_h(uint8_t* hrow, int col, float a0, float a1, float b0, float b1) {
    uint8_t* p = hrow + (col >> 3) * 2048;
    st4(p, pack_bf16(a0, a1));
    st4(p + 128, pack_bf16(b0, b1));
}

__device__ __forceinline__ void stage_h(uint32_t stage, int rg0, int lane, const float (&acc)[64]) {
#pragma unroll
    for (int j = 0; j < 8; j += 2)
        asm volatile("stmatrix.sync.aligned.m8n8.x4.shared.b16 [%0], {%1, %2, %3, %4};"
                     ::"r"(stage + (j + (lane >> 4)) * 2048 + rg0 * 128 + (lane & 15) * 16),
                       "r"(pack_bf16(acc[4 * j] * acc[32 + 4 * j], acc[4 * j + 1] * acc[33 + 4 * j])),
                       "r"(pack_bf16(acc[4 * j + 2] * acc[34 + 4 * j], acc[4 * j + 3] * acc[35 + 4 * j])),
                       "r"(pack_bf16(acc[4 * j + 4] * acc[36 + 4 * j], acc[4 * j + 5] * acc[37 + 4 * j])),
                       "r"(pack_bf16(acc[4 * j + 6] * acc[38 + 4 * j], acc[4 * j + 7] * acc[39 + 4 * j])) : "memory");
    asm volatile("fence.proxy.async.shared::cta;" ::: "memory");
}

#define RUN_TILE(K0, J0, FULLW, MMA, HOOK)                                                             \
    {                                                                                                  \
        uint32_t rdy = 0;                                                                              \
        _Pragma("unroll") for (int n = 0; n < 8; n++) {                                                \
            const int xb = ((K0) + n) & 7, J = (J0) + n;                                               \
            if (!rdy) {                                                                                \
                if ((J0) == 0) mbar_wait(bar + 8 * (B_XFULL + xb), 0);                                 \
                mbar_wait(bar + 8 * ((FULLW) + J), 0);                                                 \
            }                                                                                          \
            if (n < 7) {                                                                               \
                rdy = mbar_probe(bar + 8 * ((FULLW) + J + 1), 0);                                      \
                if ((J0) == 0) rdy &= mbar_probe(bar + 8 * (B_XFULL + ((xb + 1) & 7)), 0);             \
            }                                                                                          \
            wg_fence();                                                                                \
            _Pragma("unroll") for (int kk = 0; kk < 4; kk++) {                                         \
                const int sd = n | kk;                                                                 \
                MMA                                                                                    \
            }                                                                                          \
            wg_commit();                                                                               \
            HOOK                                                                                       \
            wg_wait<0>();                                                                              \
            mbar_arrive_lane0(bar + 8 * ((FULLW) + 32 + J), lane);                                     \
        }                                                                                              \
    }

enum { M_X, M_KV, M_Q32, M_GU32, M_GU, M_D, M_WO, M_OUT, M_COUNT };
struct Maps { CUtensorMap m[M_COUNT]; };
struct Ptrs { const uint8_t *wd, *wo, *x, *wqkv; };

__global__ void __launch_bounds__(NTHREADS, 1)
fused_kernel(const __grid_constant__ Maps maps, const uint4* __restrict__ gw, const Ptrs pf) {
    extern __shared__ __align__(1024) uint8_t smem[];
    const uint32_t sb = (uint32_t)__cvta_generic_to_shared(smem);
    const uint32_t bar = sb + SM_BAR;
    const int tid = threadIdx.x, lane = tid & 31;
    const int wid = __reduce_max_sync(~0u, tid >> 5);
    const int wg = wid >> 2, w = wid & 3;
    const int rb = blockIdx.x >> 3, cg = blockIdx.x & 7;
    const int head = blockIdx.x >> 2, qq = blockIdx.x & 3;

    const bool helper = blockIdx.x >= NCTA;
    const int p = wid - 16;
    const bool starter = p >= 0 && p < 3;
    const uint32_t fb0 = bar + 8 * (p == 0 ? B_XFULL : p == 1 ? B_AFULL : B_BFULL);
    const uint32_t dst0 = sb + (p == 0 ? SM_X : p == 1 ? SM_WA : SM_WB);
    const int cx0 = p == 1 ? cg * 64 : 0, cy0 = p == 0 ? rb * 128 : 0, cz0 = p == 2 ? cg * 2 : p;
    if (starter && lane == 0) {
        mbar_init(fb0, 1);
        mbar_init(fb0 + 8, 1);
        asm volatile("fence.proxy.async.shared::cta;" ::: "memory");
        if (!helper) {
            mbar_expect(fb0, 16384);
            tma3d(dst0, &maps.m[p], fb0, cx0, cy0, cz0);
            if (p == 2) tma3d(dst0 + 8192, &maps.m[M_GU32], fb0, cg * 160, 0, 0);
        }
    }
    if (wid < B_COUNT / 8 && lane == 0) {
        const uint32_t c = wid == 14 ? 4 : wid == 13 ? 2 : (wid == 9 || (wid == 8 && helper)) ? 16 : (wid >= 5 && wid < 9) ? 8 : 1;
        if (wid > 1 && wid != 3) { mbar_init(bar + 64 * wid, c); mbar_init(bar + 64 * wid + 8, c); }
#pragma unroll
        for (int j = 2; j < 8; j++) mbar_init(bar + 64 * wid + 8 * j, c);
    }
    if (wid == 15) *(uint4*)(smem + SM_ONES + lane * 16) = make_uint4(0x3C003C00u, 0x3C003C00u, 0x3C003C00u, 0x3C003C00u);
    if (tid == 608) asm volatile("prefetch.tensormap [%0];" ::"l"(&maps.m[M_GU]) : "memory");
    asm volatile("fence.proxy.async.shared::cta;" ::: "memory");
    __syncwarp();
    if (starter) {
        asm volatile("bar.arrive 11, 640;" ::: "memory");
        if (lane == 0 && !helper) {
            mbar_expect(fb0 + 8, 16384);
            tma3d(dst0 + 16384, &maps.m[p], fb0 + 8, cx0 + (p == 0 ? 64 : 0), cy0 + (p == 0 ? 0 : 64), cz0);
            if (p == 2) tma3d(dst0 + 16384 + 8192, &maps.m[M_GU32], fb0 + 8, cg * 160, 64, 0);
        }
        __syncwarp();
        asm volatile("bar.sync 12, 640;" ::: "memory");
    } else {
        asm volatile("bar.arrive 12, 640;" ::: "memory");
        asm volatile("bar.sync 11, 640;" ::: "memory");
    }

    if (wg == 4) {
        asm volatile("setmaxnreg.dec.sync.aligned.u32 32;");
        if (w == 3 && !helper) {
            *(uint4*)(smem + SM_GW + lane * 32) = __ldg(gw + lane * 2);
            *(uint4*)(smem + SM_GW + lane * 32 + 16) = __ldg(gw + lane * 2 + 1);
            __syncwarp();
            const int r = cg * 16 + (lane >> 1);
            float z = 0.f;
#pragma unroll 1
            for (int i = 0; i < 32; i++) {
                if (!(i & 3)) mbar_wait(bar + 8 * (B_XFULL + (i >> 2)), 0);
                const int ch = (lane & 1) * 4 + (i & 3);
                const uint4 xv = *(const uint4*)(smem + SM_X + (i >> 2) * 16384 + r * 128 + ((ch ^ (r & 7)) << 4));
                const uint4 gv = *(const uint4*)(smem + SM_GW + (i >> 2) * 128 + ch * 16);
                const uint32_t p0 = bmul2(xv.x, gv.x), p1 = bmul2(xv.y, gv.y), p2 = bmul2(xv.z, gv.z), p3 = bmul2(xv.w, gv.w);
                z += ((bf_lo(p0) + bf_hi(p0)) + (bf_lo(p1) + bf_hi(p1))) + ((bf_lo(p2) + bf_hi(p2)) + (bf_lo(p3) + bf_hi(p3)));
            }
            z += __shfl_xor_sync(~0u, z, 1);
            if (!(lane & 1)) g_gate[rb * 128 + r] = bf_round(__fdividef(1.f, 1.f + __expf(-bf_round(z))));
#pragma unroll 1
            for (int i = lane; i < 172 + 64; i += 32)
                l2_prefetch(i < 172 ? pf.wd + (size_t)blockIdx.x * 11008 + i * 64 : pf.wo + (size_t)blockIdx.x * 4096 + (i - 172) * 64);
            __syncwarp();
        }
        if (lane == 0) {
            unsigned epoch;
            asm volatile("ld.relaxed.gpu.global.u32 %0, [%1];" : "=r"(epoch) : "l"(&g_cnt[C_EPOCH * 32]) : "memory");
            if (helper) {
                const int rb0 = (blockIdx.x - NCTA) * 4;
                if (w < 3) {
#pragma unroll 1
                    for (int st = 0; st < 32; st++) {
                        const int sl = st & 3;
                        const uint32_t fb = bar + 8 * ((w == 0 ? B_XFULL : w == 1 ? B_AFULL : B_BFULL) + sl), dst = sb + sl * 49152 + w * 16384;
                        if (st >= 4) {
                            if (w != 2) mbar_wait(bar + 8 * (B_AEMPTY + sl), ((st >> 2) - 1) & 1);
                            if (w != 1) mbar_wait(bar + 8 * (B_BEMPTY + sl), ((st >> 2) - 1) & 1);
                        }
                        mbar_expect(fb, w == 2 ? 8192 : 16384);
                        if (w == 0) tma3d(dst, &maps.m[M_X], fb, (st & 7) * 64, (rb0 + (st >> 3)) * 128, 0);
                        else tma3d(dst, &maps.m[w == 1 ? M_GU : M_GU32], fb, 1280 + (w - 1) * 64, (st & 7) * 64, 0);
                    }
                    if (w == 0) {
                        cnt_wait(C_QKV + rb0 / 2, (epoch + 1) * 16);
                        cnt_wait(C_QKV + rb0 / 2 + 1, (epoch + 1) * 16);
                        mbar_arrive(bar + 8 * B_QKVOK);
                        mbar_wait(bar + 8 * B_HW, 0);
                        proxy_fence();
#pragma unroll 1
                        for (int i = 0; i < 8; i++) {
                            mbar_expect(bar + 8 * (B_KVFULL + i), HU * 8192);
                            bulk_load(sb + i * HU * 8192, g_KV + (size_t)(rb0 * 2 + i) * 131072 + (16 - HU) * 8192, HU * 8192, bar + 8 * (B_KVFULL + i));
                        }
                    }
                } else {
                    mbar_wait(bar + 8 * B_HW, 0);
                    cnt_signal(C_H + rb0);
#pragma unroll
                    for (int i = 1; i < 4; i++) asm volatile("red.relaxed.gpu.global.add.u32 [%0], 1;" ::"l"(&g_cnt[(C_H + rb0 + i) * 32]) : "memory");
#pragma unroll 1
                    for (int i = 0; i < 8; i++) {
                        mbar_wait(bar + 8 * (B_BEMPTY + 8 + i), 0);
                        cnt_signal(C_P + rb0 * 2 + i);
                    }
                }
            } else {
                if (w == 0) {
#pragma unroll 1
                    for (int i = 2; i < 8; i++) {
                        mbar_wait(bar + 8 * (B_XFULL + i - 2), 0);
                        mbar_expect(bar + 8 * (B_XFULL + i), 16384);
                        tma3d(sb + SM_X + i * 16384, &maps.m[M_X], bar + 8 * (B_XFULL + i), i * 64, rb * 128, 0);
                    }
                    mbar_wait(bar + 8 * B_QKVOK, 0);
                    proxy_fence();
#pragma unroll 1
                    for (int j = 0; j < 8; j++) {
                        mbar_wait(bar + 8 * (B_AEMPTY + 8 + j), 0);
                        mbar_wait(bar + 8 * (B_BEMPTY + 8 + j), 0);
                        mbar_expect(bar + 8 * (B_KVFULL + j), 16384);
                        bulk_load(sb + SM_X + j * 16384, g_KV + (size_t)head * 131072 + j * 16384, 16384, bar + 8 * (B_KVFULL + j));
                    }
                } else if (w == 1) {
#pragma unroll 1
                    for (int J = 2; J < 16; J++) {
                        mbar_wait(bar + 8 * (J < 3 ? B_AFULL : B_AEMPTY + J - 3), 0);
                        mbar_expect(bar + 8 * (B_AFULL + J), 16384);
                        tma3d(sb + wa_off(J), &maps.m[J < 8 ? M_KV : M_GU], bar + 8 * (B_AFULL + J), J < 8 ? cg * 64 : cg * 160 + 32, (J & 7) * 64, J < 8);
                    }
                } else if (w == 2) {
#pragma unroll 1
                    for (int J = 2; J < 16; J++) {
                        const uint32_t dst = sb + wb_off(J), fb = bar + 8 * (B_BFULL + J);
                        mbar_wait(bar + 8 * (J < 3 ? B_BFULL : B_BEMPTY + J - 3), 0);
                        mbar_expect(fb, 16384);
                        if (J < 8) {
                            tma3d(dst, &maps.m[M_Q32], fb, 0, J * 64, cg * 2);
                            tma3d(dst + 8192, &maps.m[M_GU32], fb, cg * 160, J * 64, 0);
                        } else {
                            tma3d(dst, &maps.m[M_GU], fb, cg * 160 + 96, (J - 8) * 64, 0);
                        }
                    }
                } else {
                    mbar_wait(bar + 8 * B_QKVW, 0);
                    cnt_signal(C_QKV + cg);
                    cnt_wait(C_QKV + (head >> 2), (epoch + 1) * 16);
                    mbar_arrive(bar + 8 * B_QKVOK);
                    mbar_wait(bar + 8 * B_HW, 0);
                    {
                        uint8_t* const hd = g_H + (size_t)rb * 22 * 16384 + (cg * 20 + 4) * 2048;
                        asm volatile("cp.async.bulk.global.shared::cta.bulk_group [%0], [%1], 16384;" ::"l"(hd), "r"(sb + wa_off(13)) : "memory");
                        asm volatile("cp.async.bulk.global.shared::cta.bulk_group [%0], [%1], 16384;" ::"l"(hd + 16384), "r"(sb + wb_off(13)) : "memory");
                        asm volatile("cp.async.bulk.commit_group;" ::: "memory");
                        asm volatile("cp.async.bulk.wait_group 0;" ::: "memory");
                    }
                    cnt_signal(C_H + rb);
                    cnt_wait(C_H + rb, (epoch + 1) * 9);
                    mbar_arrive(bar + 8 * B_HOK);
                    asm volatile("prefetch.tensormap [%0];" ::"l"(&maps.m[M_OUT]) : "memory");
                    cnt_wait_slow(C_P + head, epoch + 1);
                    mbar_arrive(bar + 8 * B_POK);
                }
                if (w == 1 || w == 2) {
                    mbar_wait(bar + 8 * B_HOK, 0);
                    proxy_fence();
#pragma unroll 1
                    for (int st = 0; st < 22; st++) {
                        const int d = st & 3;
                        const uint32_t fb = bar + 8 * (B_DFULL + d), dst = sb + SM_DR + d * 24576;
                        if (st >= 4) mbar_wait(bar + 8 * (B_DEMPTY + d), ((st >> 2) - 1) & 1);
                        if (w == 1) {
                            mbar_expect(fb, 8192);
                            tma2d(dst + 16384, &maps.m[M_D], fb, cg * 64, st * 64);
                        } else {
                            mbar_expect(fb, 16384);
                            bulk_load(dst, g_H + ((size_t)rb * 22 + st) * 16384, 16384, fb);
                        }
                    }
                    if (w == 1) {
                        mbar_wait(bar + 8 * (B_DEMPTY + 1), 1);
                        mbar_expect(bar + 8 * B_WOFULL, 65536);
#pragma unroll 1
                        for (int j = 0; j < 8; j++) tma2d(sb + SM_WO + j * 8192, &maps.m[M_WO], bar + 8 * B_WOFULL, cg * 64, j * 64);
                    }
                }
                if (w == 0) {
                    mbar_wait(bar + 8 * B_OWH, 0);
                    cnt_signal(C_O0 + qq * 4);
#pragma unroll
                    for (int i = 1; i < 4; i++) asm volatile("red.relaxed.gpu.global.add.u32 [%0], 1;" ::"l"(&g_cnt[(C_O0 + qq * 4 + i) * 32]) : "memory");
                    mbar_wait(bar + 8 * B_OW0, 0);
                    asm volatile("red.release.gpu.global.add.u32 [%0], 4;" ::"l"(&g_cnt[(C_O + qq * 4) * 32]) : "memory");
                    cnt_wait(C_O0 + rb, (epoch + 1) * 32);
                    proxy_fence();
                    mbar_wait(bar + 8 * B_KVFREE, 0);
#pragma unroll 1
                    for (int j = 0; j < 4; j++) {
                        mbar_expect(bar + 8 * (B_OFULL + j), 16384);
                        bulk_load(sb + SM_X + j * 16384, g_O + (size_t)rb * 131072 + j * 16384, 16384, bar + 8 * (B_OFULL + j));
                    }
                    cnt_wait(C_O + rb, (epoch + 1) * 128);
                    proxy_fence();
#pragma unroll 1
                    for (int j = 0; j < 8; j++) {
                        mbar_expect(bar + 8 * (B_OFULL + 4 + j), 8192);
                        bulk_load(sb + SM_X + 65536 + j * 8192, g_O + (size_t)rb * 131072 + 65536 + j * 8192, 8192, bar + 8 * (B_OFULL + 4 + j));
                    }
                }
            }
        }
    } else {
        asm volatile("setmaxnreg.inc.sync.aligned.u32 112;");
        const int g = lane >> 2, t = lane & 3;
        const int mi = wg & 1, pair = wg >> 1;
        uint8_t* const hrow = g_H + (size_t)rb * 22 * 16384 + (mi * 8 + w * 2) * 128 + lane * 4;
        const int lrow = mi * 64 + w * 16 + g;
        const size_t r0 = ((size_t)(cg * 4) * SEQ + rb * 128 + lrow) * 32 + t * 8;
        if (helper) {
            const int rb0 = (blockIdx.x - NCTA) * 4;
            const uint32_t dX = uni(desc_lo(sb + mi * 8192, 16));
#define HELPER_TILE(FULLW, MMA)                                                                        \
    _Pragma("unroll 1") for (int u = 0; u < 2; u++) {                                                  \
        _Pragma("unroll") for (int sl = 0; sl < 4; sl++) {                                             \
            mbar_wait(bar + 8 * (B_XFULL + sl), u);                                                    \
            mbar_wait(bar + 8 * ((FULLW) + sl), u);                                                    \
            wg_fence();                                                                                \
            _Pragma("unroll") for (int kk = 0; kk < 4; kk++) { MMA }                                   \
            wg_commit();                                                                               \
            wg_wait<1>();                                                                              \
            mbar_arrive_lane0(bar + 8 * ((FULLW) + 32 + ((sl + 3) & 3)), (sl || u) ? lane : 1);        \
        }                                                                                              \
    }                                                                                                  \
    wg_wait<0>();                                                                                      \
    mbar_arrive_lane0(bar + 8 * ((FULLW) + 32 + 3), lane);
#pragma unroll 1
            for (int i = 0; i < 4; i++) {
                uint8_t* const hr = g_H + (size_t)(rb0 + i) * 22 * 16384 + (mi * 8 + w * 2) * 128 + lane * 4;
                if (uni(pair == 0)) {
                    float acc[64];
#pragma unroll
                    for (int j = 0; j < 64; j++) acc[j] = 0.f;
                    fence_regs(acc);
                    const uint32_t dR = desc_lo(sb + 16384, 8192);
                    HELPER_TILE(B_AFULL, wg_n128_tb(acc, dX + sl * 3072 + 2 * kk, dR + sl * 3072 + 128 * kk, 1);)
                    fence_regs(acc);
#pragma unroll
                    for (int j = 0; j < 8; j++)
                        store_h(hr, 1280 + j * 8, acc[4 * j] * acc[32 + 4 * j], acc[4 * j + 1] * acc[33 + 4 * j],
                                acc[4 * j + 2] * acc[34 + 4 * j], acc[4 * j + 3] * acc[35 + 4 * j]);
                } else {
                    float acc[32];
#pragma unroll
                    for (int j = 0; j < 32; j++) acc[j] = 0.f;
                    fence_regs(acc);
                    const uint32_t dR = desc_lo(sb + 32768, 4096);
                    HELPER_TILE(B_BFULL, wg_n64_tb64(acc, dX + sl * 3072 + 2 * kk, dR + sl * 3072 + 64 * kk, 1);)
                    fence_regs(acc);
#pragma unroll
                    for (int j = 0; j < 4; j++) {
                        store_h(hr, 1344 + j * 8, acc[4 * j] * acc[16 + 4 * j], acc[4 * j + 1] * acc[17 + 4 * j],
                                acc[4 * j + 2] * acc[18 + 4 * j], acc[4 * j + 3] * acc[19 + 4 * j]);
                        store_h(hr, 1376 + j * 8, 0.f, 0.f, 0.f, 0.f);
                    }
                }
            }
        }
        uint32_t qa[4];
        auto load_q = [&](int hrow0) {
            const int l = fresh_tid() & 31;
            const uint8_t* qp = g_Q + (size_t)(hrow0 + w * 16 + (l >> 2)) * 32 + (l & 3) * 4;
            qa[0] = ld4(qp); qa[1] = ld4(qp + 256); qa[2] = ld4(qp + 16); qa[3] = ld4(qp + 256 + 16);
        };
        if (helper) {
            mbar_wait(bar + 8 * B_QKVOK, 0);
            load_q(((blockIdx.x - NCTA) * 32 + wg) * 512 + 7 * 64);
            __nanosleep(wg * 500);
        } else if (pair == 0) {
            float acc[64];
            const uint32_t dX = uni(desc_lo(sb + SM_X + mi * 8192, 16)), dR = desc_lo(sb, 8192);
            RUN_TILE(0, 0, B_AFULL, wg_n128_tb(acc, dX + xb * 1024 + 2 * kk, dR + wa_off(J) / 16 + 128 * kk, sd);, )
            fence_regs(acc);
            uint32_t pk[32];
#pragma unroll
            for (int h = 0; h < 4; h++) {
                const float* k = acc + h * 8; const float* v = acc + 32 + h * 8;
                pk[8 * h + 0] = pack_bf16(k[0], k[1]); pk[8 * h + 1] = pack_bf16(k[4], k[5]);
                pk[8 * h + 2] = pack_bf16(k[2], k[3]); pk[8 * h + 3] = pack_bf16(k[6], k[7]);
                pk[8 * h + 4] = pack_f16(v[0], v[1]); pk[8 * h + 5] = pack_f16(v[4], v[5]);
                pk[8 * h + 6] = pack_f16(v[2], v[3]); pk[8 * h + 7] = pack_f16(v[6], v[7]);
            }
            uint8_t* const kp = g_KV + ((size_t)(cg * 4) * 16 + rb) * 8192 + lrow * 32 + (((t >> 1) ^ ((g >> 2) & 1)) << 4) + (t & 1) * 8;
            RUN_TILE(0, 8, B_AFULL, wg_n128_tb(acc, dX + xb * 1024 + 2 * kk, dR + wa_off(J) / 16 + 128 * kk, sd);,
                     _Pragma("unroll") for (int i = n * SPA; i < n * SPA + SPA && i < 16; i++)
                         st8(kp + (i >> 2) * 131072 + ((i >> 1) & 1) * 4096 + (i & 1) * 256, pk[2 * i], pk[2 * i + 1]);
                     if (n == 15 / SPA) { __syncwarp(); mbar_arrive_lane0(bar + 8 * B_QKVW, lane); }
                     if (n == 7) { mbar_wait(bar + 8 * B_QKVOK, 0); load_q(head * SEQ + qq * 512 + wg * 64); })
            fence_regs(acc);
            mbar_wait(bar + 8 * (B_AEMPTY + 13), 0);
            stage_h(sb + wa_off(13), mi * 8 + w * 2, lane, acc);
        } else {
            float acc[64];
            const uint32_t dX = uni(desc_lo(sb + SM_X + mi * 8192, 16)), dR = desc_lo(sb, 8192), dN = desc_lo(sb, 4096);
            RUN_TILE(0, 0, B_BFULL, wg_n128_tb64(acc, dX + xb * 1024 + 2 * kk, dN + wb_off(J) / 16 + 64 * kk, sd);, )
            fence_regs(acc);
            uint32_t pk[24];
            const float qs = 0.25f * 1.4426950408889634f;
#pragma unroll
            for (int h = 0; h < 4; h++) {
                const float* q = acc + h * 8;
                pk[4 * h + 0] = pack_bf16(q[0] * qs, q[1] * qs); pk[4 * h + 1] = pack_bf16(q[4] * qs, q[5] * qs);
                pk[4 * h + 2] = pack_bf16(q[2] * qs, q[3] * qs); pk[4 * h + 3] = pack_bf16(q[6] * qs, q[7] * qs);
            }
#pragma unroll
            for (int j = 0; j < 8; j++) pk[16 + j] = pack_bf16(acc[32 + 2 * j] * acc[48 + 2 * j], acc[33 + 2 * j] * acc[49 + 2 * j]);
            uint8_t* const qp = g_Q + r0;
            uint8_t* const hp = hrow + cg * 20 * 2048;
            RUN_TILE(0, 8, B_BFULL, wg_n128_tb(acc, dX + xb * 1024 + 2 * kk, dR + wb_off(J) / 16 + 128 * kk, sd);,
                     _Pragma("unroll") for (int i = n * SPB; i < n * SPB + SPB && i < 8; i++)
                         st8(qp + (i >> 1) * (SEQ * 32) + (i & 1) * 256, pk[2 * i], pk[2 * i + 1]);
                     if (n == 7 / SPB) { __syncwarp(); mbar_arrive_lane0(bar + 8 * B_QKVW, lane); }
                     if (n == 4 || n == 5) {
                         st4(hp + (2 * n - 8) * 2048, pk[4 * n]); st4(hp + (2 * n - 8) * 2048 + 128, pk[4 * n + 1]);
                         st4(hp + (2 * n - 7) * 2048, pk[4 * n + 2]); st4(hp + (2 * n - 7) * 2048 + 128, pk[4 * n + 3]);
                     }
                     if (n == 7) { mbar_wait(bar + 8 * B_QKVOK, 0); load_q(head * SEQ + qq * 512 + 64); })
            fence_regs(acc);
            mbar_wait(bar + 8 * (B_BEMPTY + 13), 0);
            stage_h(sb + wb_off(13), mi * 8 + w * 2, lane, acc);
        }
        __syncwarp();
        mbar_arrive_lane0(bar + 8 * B_HW, lane);

        {
            const uint32_t one2 = *(volatile uint32_t*)(smem + SM_ONES);
            float o[12];
#pragma unroll 1
            for (int sg = 0; sg < (helper ? 8 : 3); sg++) {
                int mt = wg ? 2 * wg + sg - 1 : sg >> 1, c0 = 0, c1 = 16;
                if (wg == 0) { c0 = sg == 0 ? 0 : sg == 1 ? 8 : PC1 + PC2 + PC3; if (sg == 0) c1 = 8; }
                else if (sg == 0) { mt = 1; c0 = wg == 1 ? 0 : wg == 2 ? PC1 : PC1 + PC2; c1 = wg == 1 ? PC1 : wg == 2 ? PC1 + PC2 : PC1 + PC2 + PC3; }
                else if (sg == 2 && wg == 3) c1 = 16 - HU;
                const int hcta = (blockIdx.x - NCTA) * 32 + sg * 4 + wg;
                if (helper) {
                    c0 = sg * HU; c1 = c0 + HU;
                    mbar_wait(bar + 8 * (B_KVFULL + sg), 0);
                } else if (sg < 2) {
                    for (int j = c0 >> 1; j <= (c1 - 1) >> 1; j++) mbar_wait(bar + 8 * (B_KVFULL + j), 0);
                }
                if (uni(wg != 0 || sg != 1 || helper)) {
                    if (sg && !helper) load_q(head * SEQ + qq * 512 + mt * 64);
#pragma unroll
                    for (int i = 0; i < 12; i++) o[i] = 0.f;
                }
                attn_range(o, qa, sb, one2, c0, c1);
                const int lt = fresh_tid() & 127, lane = lt & 31, g = lane >> 2, t = lane & 3;
                const int row = qq * 512 + mt * 64 + w * 16 + g;
                if (uni(!helper && sg == 0 && wg == 0)) continue;
                o[9] = o[10];
                float* part = g_part + (size_t)(helper ? hcta : blockIdx.x) * 4 * 1280 + lt;
                if (uni(sg == 0 || helper)) {
                    if (helper && sg < 7) load_q((hcta + 4) * 512 + 7 * 64);
#pragma unroll
                    for (int i = 0; i < 10; i++) part[((helper ? 3 : wg - 1) * 10 + i) * 128] = o[i];
                    if (helper) { __syncwarp(); mbar_arrive_lane0(bar + 8 * (B_BEMPTY + 8 + sg), lane); }
                    else asm volatile("bar.arrive 5, 512;" ::: "memory");
                    continue;
                }
                if (uni((wg == 0 || wg == 3) && sg == 2)) {
                    if (wg == 0) asm volatile("bar.sync 5, 512;" ::: "memory");
                    else mbar_wait(bar + 8 * B_POK, 0);
                    const float* pp = part + wg * 1280;
#pragma unroll
                    for (int i = 0; i < 10; i++) {
                        float v0, v1 = 0.f, v2 = 0.f;
                        asm volatile("ld.global.cg.f32 %0, [%1];" : "=f"(v0) : "l"(pp + i * 128) : "memory");
                        if (wg == 0) {
                            asm volatile("ld.global.cg.f32 %0, [%1];" : "=f"(v1) : "l"(pp + (10 + i) * 128) : "memory");
                            asm volatile("ld.global.cg.f32 %0, [%1];" : "=f"(v2) : "l"(pp + (20 + i) * 128) : "memory");
                        }
                        o[i] += v0 + (v1 + v2);
                    }
                }
                float i0 = __fdividef(1.f, o[8]), i1 = __fdividef(1.f, o[9]);
                {
                    float m0 = fmaxf(fmaxf(fabsf(o[0]), fabsf(o[1])), fmaxf(fabsf(o[4]), fabsf(o[5])));
                    float m1 = fmaxf(fmaxf(fabsf(o[2]), fabsf(o[3])), fmaxf(fabsf(o[6]), fabsf(o[7])));
                    const float chk = ((o[0] + o[1]) + (o[2] + o[3])) + ((o[4] + o[5]) + (o[6] + o[7]));
                    m0 = fmaxf(m0, __shfl_xor_sync(~0u, m0, 1)); m0 = fmaxf(m0, __shfl_xor_sync(~0u, m0, 2));
                    m1 = fmaxf(m1, __shfl_xor_sync(~0u, m1, 1)); m1 = fmaxf(m1, __shfl_xor_sync(~0u, m1, 2));
                    bool ok = o[8] >= 64.f && o[8] < 1e30f && o[9] >= 64.f && o[9] < 1e30f && fabsf(chk) < 1e37f &&
                              m0 * i0 >= 1.2207e-4f && m1 * i1 >= 1.2207e-4f;
                    if (uni(wg_any(wg, !ok))) {
                        float tmp[10];
                        attn_generic(tmp, qa[0], qa[1], qa[2], qa[3], head, pf.x, pf.wqkv);
#pragma unroll
                        for (int i = 0; i < 10; i++) o[i] = tmp[i];
                        i0 = 1.f / o[8]; i1 = 1.f / o[9];
                    }
                }
                uint8_t* op = g_O + (size_t)(row >> 6) * 65536 + (head * 2 + (t & 1)) * 1024 + (row & 63) * 16 + (t >> 1) * 4;
                st4(op, pack_bf16(o[0] * i0, o[1] * i0));
                st4(op + 8, pack_bf16(o[4] * i0, o[5] * i0));
                st4(op + 128, pack_bf16(o[2] * i1, o[3] * i1));
                st4(op + 128 + 8, pack_bf16(o[6] * i1, o[7] * i1));
                __syncwarp();
                mbar_arrive_lane0(bar + 8 * B_OWH, sg == 1 ? lane : 1);
            }
            if (helper) return;
        }
        {
            const int lane = fresh_tid() & 31;
            __syncwarp();
            if (lane == 0) {
                if (wg == 0) mbar_arrive(bar + 8 * B_OW0);
                else cnt_signal(C_O + qq * 4 + wg);
                mbar_arrive(bar + 8 * B_KVFREE);
            }
        }

        if (wg == 0) {
            const int lt = fresh_tid() & 127, lane = lt & 31, t = lane & 3;
            float acc[64];
            const uint32_t dH = desc_lo(sb + SM_DR, 2048), dW = desc_lo(sb + SM_DR + 16384, 16);
            float gv = 0.f;
#pragma unroll 1
            for (int u = 0; u < 6; u++) {
#pragma unroll
                for (int sl = 0; sl < 4; sl++) {
                    if (sl == 2 && u == 5) break;
                    mbar_wait(bar + 8 * (B_DFULL + sl), u & 1);
                    if (sl == 0 && u == 0) {
                        asm volatile("ld.global.cg.f32 %0, [%1];" : "=f"(gv) : "l"(g_gate + rb * 128 + lt) : "memory");
                    }
                    wg_fence();
#pragma unroll
                    for (int kk = 0; kk < 4; kk++)
                        wg_n128_ta(acc, dW + sl * 1536 + 128 * kk, dH + sl * 1536 + 256 * kk, (sl | kk) ? 1 : u);
                    wg_commit();
                    wg_wait<1>();
                    mbar_arrive_lane0(bar + 8 * (B_DEMPTY + ((sl + 3) & 3)), (sl || u) ? lane : 1);
                }
            }
            wg_wait<0>();
            fence_regs(acc);
            mbar_arrive_lane0(bar + 8 * (B_DEMPTY + 1), lane);
            *(float*)(smem + SM_G + lt * 4) = gv;
            wg_bar(0);
#pragma unroll
            for (int j = 0; j < 16; j++) {
                const float2 gg = *(const float2*)(smem + SM_G + (8 * j + 2 * t) * 4);
                const float u0 = bf_round(1.f - gg.x), u1 = bf_round(1.f - gg.y);
                *(float4*)(smem + SM_BP + (j * 128 + lt) * 16) = make_float4(acc[4 * j] * u0, acc[4 * j + 1] * u1, acc[4 * j + 2] * u0, acc[4 * j + 3] * u1);
            }
            __syncwarp();
            mbar_arrive_lane0(bar + 8 * B_BREADY, lane);
        }

        if (wg >= 2) {
            const int hf = wg - 2, lt = fresh_tid() & 127, lane = lt & 31, t = lane & 3;
            float acc[32];
            const uint32_t dW = desc_lo(sb + SM_WO, 16), dO = uni(desc_lo(sb + SM_X + hf * 65536, 1024));
            const uint32_t ob = uni(bar + 8 * (B_OFULL + hf * 4));
            mbar_wait(bar + 8 * B_BREADY, 0);
            float4 bp[8];
            float2 gg[8];
#pragma unroll
            for (int j = 0; j < 8; j++) {
                bp[j] = *(const float4*)(smem + SM_BP + hf * 16384 + (j * 128 + lt) * 16);
                gg[j] = *(const float2*)(smem + SM_G + (hf * 64 + 8 * j + 2 * t) * 4);
            }
            wg_bar(wg);
            mbar_wait(bar + 8 * B_WOFULL, 0);
#pragma unroll
            for (int j = 0; j < 8; j++) {
                mbar_wait(ob + 8 * (hf ? j : j >> 1), 0);
                wg_fence();
#pragma unroll
                for (int kk = 0; kk < 4; kk++) wg_n64_ta(acc, dW + j * 512 + 128 * kk, dO + j * 512 + 128 * kk, j | kk);
                wg_commit();
            }
            wg_wait<0>();
            fence_regs(acc);
            const uint32_t stg = sb + SM_BP + hf * 16384;
#pragma unroll
            for (int j = 0; j < 8; j += 2) {
                const uint32_t r0 = pack_bf16(fmaf(acc[4 * j], gg[j].x, bp[j].x), fmaf(acc[4 * j + 1], gg[j].y, bp[j].y));
                const uint32_t r1 = pack_bf16(fmaf(acc[4 * j + 2], gg[j].x, bp[j].z), fmaf(acc[4 * j + 3], gg[j].y, bp[j].w));
                const uint32_t r2 = pack_bf16(fmaf(acc[4 * j + 4], gg[j + 1].x, bp[j + 1].x), fmaf(acc[4 * j + 5], gg[j + 1].y, bp[j + 1].y));
                const uint32_t r3 = pack_bf16(fmaf(acc[4 * j + 6], gg[j + 1].x, bp[j + 1].z), fmaf(acc[4 * j + 7], gg[j + 1].y, bp[j + 1].w));
                const int orow = 8 * (j + (lane >> 4)) + (lane & 7), ch = 2 * w + ((lane >> 3) & 1);
                asm volatile("stmatrix.sync.aligned.m8n8.x4.trans.shared.b16 [%0], {%1, %2, %3, %4};"
                             ::"r"(stg + orow * 128 + ((ch ^ (lane & 7)) << 4)), "r"(r0), "r"(r1), "r"(r2), "r"(r3) : "memory");
            }
            asm volatile("fence.proxy.async.shared::cta;" ::: "memory");
            wg_bar(wg);
            if (lt == 0) {
                asm volatile("cp.async.bulk.tensor.2d.global.shared::cta.bulk_group [%0, {%2, %3}], [%1];"
                             ::"l"(&maps.m[M_OUT]), "r"(stg), "r"(cg * 64), "r"(rb * 128 + hf * 64) : "memory");
                asm volatile("cp.async.bulk.commit_group;" ::: "memory");
                asm volatile("cp.async.bulk.wait_group.read 0;" ::: "memory");
                if (blockIdx.x == 0 && hf == 1) asm volatile("red.relaxed.gpu.global.add.u32 [%0], 1;" ::"l"(&g_cnt[C_EPOCH * 32]) : "memory");
            }
        }
    }
}

typedef CUresult (*EncodeFn)(CUtensorMap*, CUtensorMapDataType, cuuint32_t, void*, const cuuint64_t*, const cuuint64_t*,
                             const cuuint32_t*, const cuuint32_t*, CUtensorMapInterleave, CUtensorMapSwizzle,
                             CUtensorMapL2promotion, CUtensorMapFloatOOBfill);

void make_map(EncodeFn enc, CUtensorMap* m, const void* p, int rank, const cuuint64_t* dims, const cuuint64_t* strides, const cuuint32_t* box,
              CUtensorMapSwizzle sw = CU_TENSOR_MAP_SWIZZLE_128B) {
    const cuuint32_t es[3] = {1, 1, 1};
    enc(m, CU_TENSOR_MAP_DATA_TYPE_BFLOAT16, rank, const_cast<void*>(p), dims, strides, box, es, CU_TENSOR_MAP_INTERLEAVE_NONE,
        sw, CU_TENSOR_MAP_L2_PROMOTION_L2_128B, CU_TENSOR_MAP_FLOAT_OOB_FILL_NONE);
}
void make_map2(EncodeFn enc, CUtensorMap* m, const void* p, uint64_t cols, uint64_t rows, uint32_t bc, uint32_t br) {
    const cuuint64_t d[2] = {cols, rows}, s[1] = {cols * 2};
    const cuuint32_t b[2] = {bc, br};
    make_map(enc, m, p, 2, d, s, b);
}

}

extern "C" void kernel_launch(void* const* d_in, const int* in_sizes, int n_in, void* d_out, int out_size) {
    (void)in_sizes; (void)n_in; (void)out_size;
    void* fn = nullptr;
    cudaDriverEntryPointQueryResult qr;
    cudaGetDriverEntryPoint("cuTensorMapEncodeTiled", &fn, cudaEnableDefault, &qr);
    EncodeFn enc = (EncodeFn)fn;
    Maps maps;
    CUtensorMap &tmX = maps.m[M_X], &tmKV = maps.m[M_KV], &tmGU = maps.m[M_GU], &tmD = maps.m[M_D], &tmWO = maps.m[M_WO], &tmOut = maps.m[M_OUT];
    {
        const cuuint64_t d[3] = {512, 2048, 1}, st[2] = {1024, 2048 * 1024};
        const cuuint32_t b[3] = {64, 128, 1};
        make_map(enc, &tmX, d_in[0], 3, d, st, b);
    }
    {
        const cuuint64_t d[3] = {512, 512, 3}, st[2] = {3072, 1024};
        const cuuint32_t b[3] = {64, 64, 2};
        make_map(enc, &tmKV, d_in[1], 3, d, st, b);
        const cuuint64_t dq[3] = {32, 512, 48}, sq[2] = {3072, 64};
        const cuuint32_t b32[3] = {32, 64, 2};
        make_map(enc, &maps.m[M_Q32], d_in[1], 3, dq, sq, b32, CU_TENSOR_MAP_SWIZZLE_64B);
        const uint8_t *pg = (const uint8_t*)d_in[4], *pu = (const uint8_t*)d_in[5];
        const cuuint64_t d2[3] = {1376, 512, 2}, st2[2] = {2752, (cuuint64_t)(pg < pu ? pu - pg : pg - pu)};
        const cuuint32_t b2[3] = {64, 64, 2};
        make_map(enc, &tmGU, pg < pu ? pg : pu, 3, d2, st2, b2);
        make_map(enc, &maps.m[M_GU32], pg < pu ? pg : pu, 3, d2, st2, b32, CU_TENSOR_MAP_SWIZZLE_64B);
    }
    make_map2(enc, &tmD, d_in[6], 512, 1376, 64, 64);
    make_map2(enc, &tmWO, d_in[2], 512, 512, 64, 64);
    make_map2(enc, &tmOut, d_out, 512, 2048, 64, 64);
    cudaFuncSetAttribute(fused_kernel, cudaFuncAttributeMaxDynamicSharedMemorySize, SM_TOTAL);
    fused_kernel<<<NCTA + NHELP, NTHREADS, SM_TOTAL>>>(maps, (const uint4*)d_in[7],
        Ptrs{(const uint8_t*)d_in[6], (const uint8_t*)d_in[2], (const uint8_t*)d_in[0], (const uint8_t*)d_in[1]});
}
```
